```python
import torch

def _softmax(x, axis=-1):
    return torch.softmax(x, dim=axis)
def _gelu(x):
    return torch.nn.functional.gelu(x, approximate="tanh")
def _silu(x):
    return torch.nn.functional.silu(x)
def _sigmoid(x):
    return torch.sigmoid(x)
def _layernorm(x, axis=-1, eps=1e-5):
    m = x.mean(dim=axis, keepdim=True)
    v = x.var(dim=axis, keepdim=True, unbiased=False)
    return (x - m) / torch.sqrt(v + eps)
def _scatter_add(tgt, idx, src, axis=0):
    return tgt.clone().index_add_(axis, idx, src)
def _segment_sum(src, seg, n):
    out = torch.zeros((n,) + src.shape[1:], dtype=src.dtype)
    return out.index_add_(0, seg, src)
def _pad(x, pw):
    flat = tuple(v for pair in reversed(pw) for v in pair)
    return torch.nn.functional.pad(x, flat)

kernel_name = 'recurrent_scan__sliding_block_cached__glu_gated_swiglu__decode'

def setup_inputs():

    _w = (lambda a: (lambda t: t.to(torch.bfloat16) if t.is_floating_point() else t)(torch.as_tensor(a)))
    def _A_setup():
        B, Sq, D = 1, 1, 640
        Hq, Hkv, Sk, Dh = 32, 32, 32768, 192
        assert Hq % Hkv == 0, (Hq, Hkv)
        return {
            "x": _w((lambda *s: torch.randn(*s, dtype=torch.bfloat16) * 0.05)(B, Sq, D)),
            "k_cache": _w((lambda *s: torch.randn(*s, dtype=torch.bfloat16) * 3.2)(B, Hkv, Sk, Dh)),
            "v_cache": _w((lambda *s: torch.randn(*s, dtype=torch.bfloat16) * 3.2)(B, Hkv, Sk, Dh)),
            "wq": _w((lambda *s: torch.randn(*s, dtype=torch.bfloat16) * 3.2)(D, Hq * Dh) * (D ** -0.5)),
            "wo": _w((lambda *s: torch.randn(*s, dtype=torch.bfloat16) * 3.2)(Hq * Dh, D) * ((Hq * Dh) ** -0.5)),
        }
    _A_in = _A_setup()

    def _B_setup():
        B, S, D, F = 1, 1, 640, 1536
        return {
            "x": _w((lambda *s: torch.randn(*s, dtype=torch.bfloat16) * 0.05)(B, S, D)),
            "w1": _w((lambda *s: torch.randn(*s, dtype=torch.bfloat16) * 0.4)(D, F) * (2.0 / D) ** 0.5),
            "w3": _w((lambda *s: torch.randn(*s, dtype=torch.bfloat16) * 0.4)(D, F) * (2.0 / D) ** 0.5),
            "w2": _w((lambda *s: torch.randn(*s, dtype=torch.bfloat16) * 0.4)(F, D) * (2.0 / F) ** 0.5),
        }
    _B_in = _B_setup()

    return {
        "A_x": _A_in["x"],
        "A_k_cache": _A_in["k_cache"],
        "A_v_cache": _A_in["v_cache"],
        "A_wq": _A_in["wq"],
        "A_wo": _A_in["wo"],
        "B_x": _B_in["x"],
        "B_w1": _B_in["w1"],
        "B_w3": _B_in["w3"],
        "B_w2": _B_in["w2"],
    }

def reference(A_x, A_k_cache, A_v_cache, A_wq, A_wo, B_x, B_w1, B_w3, B_w2):
    def _A_ref(x, k_cache, v_cache, wq, wo):
        B, Sq, D = x.shape
        Hq, Dh = 32, 192
        Hkv, Sk = k_cache.shape[1], k_cache.shape[2]
        W = min(4096, max(256, Sk // 4))
        rep = Hq // Hkv
        q = (lambda x, *d: x.permute(*d))((x @ wq).reshape(B, Sq, Hq, Dh), 0, 2, 1, 3)
        k = (lambda x, n, axis: torch.repeat_interleave(x, n, dim=axis))(k_cache[:, :, Sk - W:, :], rep, axis=1)
        v = (lambda x, n, axis: torch.repeat_interleave(x, n, dim=axis))(v_cache[:, :, Sk - W:, :], rep, axis=1)
        scores = torch.einsum("bhqd,bhkd->bhqk", q, k) * (Dh ** -0.5)
        p = _softmax(scores, axis=-1)
        o = torch.einsum("bhqk,bhkd->bhqd", p, v)
        return (lambda x, *d: x.permute(*d))(o, 0, 2, 1, 3).reshape(B, Sq, Hq * Dh) @ wo

    def _B_ref(x, w1, w3, w2):
        gate = torch.einsum("bsd,df->bsf", x, w1)
        up = torch.einsum("bsd,df->bsf", x, w3)
        h = _silu(gate) * up
        out = torch.einsum("bsf,fd->bsd", h, w2)
        return out

    x = A_x
    xn = _layernorm(x, axis=-1)
    s = _A_ref(xn, A_k_cache, A_v_cache, A_wq, A_wo)
    g = _silu(_B_ref(xn, B_w1, B_w3, B_w2))
    return x + s * g
```

```cpp
#include <cuda_runtime.h>
#include <cuda_bf16.h>
#include <cuda.h>
#include <stdint.h>

namespace {

constexpr int D_MODEL = 640;
constexpr int N_HEAD = 32;
constexpr int D_HEAD = 192;
constexpr int SEQ = 32768;
constexpr int WIN = 4096;
constexpr int D_FF = 1536;

constexpr int CL = 8;
constexpr int N_CL = 15;
constexpr int N_CTA = CL * N_CL;
constexpr int N_OWN = 10;
constexpr int N_FFN = 3;
constexpr int TILE_BYTES = 12288;
constexpr int PIECE_BYTES = TILE_BYTES / 2;
constexpr int N_SLOT = 16;
constexpr int HEAD_TILES = WIN / CL / 32;
constexpr int W_TILES = 14;
constexpr int TAIL_TILES = 10;
constexpr int POS_K2 = 5, POS_K3 = 8;

constexpr int N_CONS_WARPS = 8;
constexpr int N_CONS = N_CONS_WARPS * 32;
constexpr int N_GATHER = 128;
constexpr int N_THREADS = N_CONS + 64 + N_GATHER;
constexpr int V_WARPS = 6;
constexpr int RELEASE = 24;

constexpr double PACE_HEAD = 490, PACE_MID = 478, PACE_TAIL = 450, PACE_REF_GBS = 3352.32;
constexpr int START_DELAY = 300;
constexpr int INFLIGHT = 10;
constexpr int GATE_EARLY = 4;
constexpr int GATE_LATE = 3;
constexpr int LATE_EARLY = 2;

constexpr unsigned SPIN_LIMIT = 1u << 22;

constexpr int SM_RING = 0;
constexpr int SM_BAR = N_SLOT * TILE_BYTES;
constexpr int BAR_FULL = 0, BAR_EMPTY = 128, BAR_GO = 256, BAR_Q = 272, BAR_ML = 280, BAR_O = 288, BAR_G = 312, BAR_S = 320;
constexpr int SM_T0 = SM_BAR + 448, SM_EPOCH = SM_BAR + 452;
constexpr int SM_XN = SM_BAR + 512;
constexpr int SM_Q = SM_XN + 1408;
constexpr int SM_ST = SM_Q + 1152;
constexpr int SM_ML = SM_ST + 512;
constexpr int SM_P = SM_ML + 256;
constexpr int SM_QP = SM_P + 3072;
constexpr int SM_OP = SM_QP + 12288;
constexpr int SM_OV = SM_OP + 3072;
constexpr int SM_FG = SM_OV + 1920;
constexpr int SM_FS = SM_FG + 1024;
constexpr int SM_ALLOC = SM_FS + 1024 + 1024;

constexpr int XO_H = 32;
constexpr int XO_O = XO_H + D_FF;
constexpr int XO_END = XO_O + N_HEAD * D_HEAD;
__device__ __align__(128) uint32_t g_scratch[XO_END];

__device__ __forceinline__ uint32_t smem_u32(const void* p) { return (uint32_t)__cvta_generic_to_shared(p); }

__device__ __forceinline__ void mbar_init(uint32_t bar, uint32_t cnt) {
    asm volatile("mbarrier.init.shared::cta.b64 [%0], %1;" ::"r"(bar), "r"(cnt) : "memory");
}
__device__ __forceinline__ void mbar_expect_tx(uint32_t bar, uint32_t bytes) {
    asm volatile("mbarrier.arrive.expect_tx.shared::cta.b64 _, [%0], %1;" ::"r"(bar), "r"(bytes) : "memory");
}
__device__ __forceinline__ void mbar_arrive(uint32_t bar) {
    asm volatile("mbarrier.arrive.shared::cta.b64 _, [%0];" ::"r"(bar) : "memory");
}
__device__ __forceinline__ void mbar_wait(uint32_t bar, uint32_t parity) {
    asm volatile(
        "{\n.reg .pred p;\n.reg .u32 n;\n"
        "mov.u32 n, 0;\n"
        "WAIT_LOOP:\n"
        "mbarrier.try_wait.parity.shared::cta.b64 p, [%0], %1;\n"
        "@p bra WAIT_DONE;\n"
        "add.u32 n, n, 1;\n"
        "setp.lt.u32 p, n, %2;\n"
        "@p bra WAIT_LOOP;\n"
        "WAIT_DONE:\n}"
        ::"r"(bar), "r"(parity), "n"(SPIN_LIMIT) : "memory");
}
__device__ __forceinline__ void named_sync(int id, int n) {
    asm volatile("bar.sync %0, %1;" ::"r"(id), "r"(n) : "memory");
}
__device__ __forceinline__ void named_arrive(int id, int n) {
    asm volatile("bar.arrive %0, %1;" ::"r"(id), "r"(n) : "memory");
}
__device__ __forceinline__ uint64_t stream_policy() {
    uint64_t pol;
    asm volatile("createpolicy.fractional.L2::evict_first.b64 %0, 1.0;" : "=l"(pol));
    return pol;
}
__device__ __forceinline__ void bulk_load(uint32_t dst, const void* src, uint32_t bytes, uint32_t bar, uint64_t pol) {
    asm volatile("cp.async.bulk.shared::cluster.global.mbarrier::complete_tx::bytes.L2::cache_hint [%0], [%1], %2, [%3], %4;"
                 ::"r"(dst), "l"(src), "r"(bytes), "r"(bar), "l"(pol) : "memory");
}
__device__ __forceinline__ void tma_3d(uint32_t dst, const CUtensorMap* tm, int c0, int c1, int c2, uint32_t bar, uint64_t pol) {
    asm volatile("cp.async.bulk.tensor.3d.shared::cluster.global.mbarrier::complete_tx::bytes.L2::cache_hint [%0], [%1, {%3, %4, %5}], [%2], %6;"
                 ::"r"(dst), "l"(tm), "r"(bar), "r"(c0), "r"(c1), "r"(c2), "l"(pol) : "memory");
}
__device__ __forceinline__ void prefetch_tmap(const CUtensorMap* tm) {
    asm volatile("prefetch.tensormap [%0];" ::"l"(tm) : "memory");
}
__device__ __forceinline__ void ldsm_x4(uint32_t (&r)[4], uint32_t addr) {
    asm volatile("ldmatrix.sync.aligned.m8n8.x4.shared.b16 {%0,%1,%2,%3}, [%4];"
                 : "=r"(r[0]), "=r"(r[1]), "=r"(r[2]), "=r"(r[3]) : "r"(addr) : "memory");
}
__device__ __forceinline__ void ldsm_x4_t(uint32_t (&r)[4], uint32_t addr) {
    asm volatile("ldmatrix.sync.aligned.m8n8.x4.trans.shared.b16 {%0,%1,%2,%3}, [%4];"
                 : "=r"(r[0]), "=r"(r[1]), "=r"(r[2]), "=r"(r[3]) : "r"(addr) : "memory");
}
__device__ __forceinline__ void mma_bf16(float (&c)[4], const uint32_t (&a)[4], uint32_t b0, uint32_t b1) {
    asm volatile("mma.sync.aligned.m16n8k16.row.col.f32.bf16.bf16.f32 {%0,%1,%2,%3}, {%4,%5,%6,%7}, {%8,%9}, {%0,%1,%2,%3};"
                 : "+f"(c[0]), "+f"(c[1]), "+f"(c[2]), "+f"(c[3])
                 : "r"(a[0]), "r"(a[1]), "r"(a[2]), "r"(a[3]), "r"(b0), "r"(b1));
}
__device__ __forceinline__ float bf16r(float v) {
    uint32_t p;
    asm("cvt.rn.bf16x2.f32 %0, %1, %2;" : "=r"(p) : "f"(v), "f"(0.f));
    return __uint_as_float(p);
}
__device__ __forceinline__ uint32_t lds32(uint32_t addr) {
    uint32_t v;
    asm volatile("ld.shared.b32 %0, [%1];" : "=r"(v) : "r"(addr) : "memory");
    return v;
}
__device__ __forceinline__ float bf_lo(uint32_t v) { return __uint_as_float(v << 16); }
__device__ __forceinline__ float bf_hi(uint32_t v) { return __uint_as_float(v & 0xffff0000u); }
__device__ __forceinline__ uint32_t pack_bf16(float lo, float hi) {
    const __nv_bfloat162 p = __floats2bfloat162_rn(lo, hi);
    return *reinterpret_cast<const uint32_t*>(&p);
}
__device__ __forceinline__ uint32_t now_ns() {
    unsigned long long t;
    asm volatile("mov.u64 %0, %%globaltimer;" : "=l"(t));
    return (uint32_t)t;
}

__device__ __forceinline__ void wait_until(uint32_t t_start, uint32_t deadline) {
    unsigned n = 0;
    while (now_ns() - t_start < deadline && ++n < SPIN_LIMIT) {}
}

__device__ __forceinline__ uint32_t ll_bad4(const uint4& v, uint32_t tag) {
    uint32_t lo, hi;
    asm("lop3.b32 %0, %1, %2, %3, 0x7E;" : "=r"(lo) : "r"(v.x), "r"(v.y), "r"(tag));
    asm("lop3.b32 %0, %1, %2, %3, 0x7E;" : "=r"(hi) : "r"(v.z), "r"(v.w), "r"(tag));
    return (lo | hi) & 3u;
}
__device__ __forceinline__ float ex2(float v) {
    float r;
    asm("ex2.approx.ftz.f32 %0, %1;" : "=f"(r) : "f"(v));
    return r;
}
__device__ __forceinline__ float rcp(float v) {
    float r;
    asm("rcp.approx.ftz.f32 %0, %1;" : "=f"(r) : "f"(v));
    return r;
}
constexpr float LOG2E = 1.4426950408889634f;
__device__ __forceinline__ void ll_store(uint32_t* p, uint32_t w) {
    asm volatile("st.relaxed.gpu.global.b32 [%0], %1;" ::"l"(p), "r"(w) : "memory");
}
__device__ __forceinline__ uint32_t ll_ld(const uint32_t* p) {
    uint32_t v;
    asm volatile("ld.relaxed.gpu.global.b32 %0, [%1];" : "=r"(v) : "l"(p) : "memory");
    return v;
}
__device__ __forceinline__ float pick4(float a, float b, float c, float d, int j) {
    const float lo = (j & 1) ? b : a, hi = (j & 1) ? d : c;
    return (j & 2) ? hi : lo;
}
__device__ __forceinline__ float silu_f(float v) { return v * rcp(1.f + ex2(-LOG2E * v)); }

__device__ __forceinline__ void mbar_arrive_n(uint32_t bar, uint32_t n) {
    asm volatile("mbarrier.arrive.shared::cta.b64 _, [%0], %1;" ::"r"(bar), "r"(n) : "memory");
}
__device__ __forceinline__ uint32_t mapa(uint32_t addr, uint32_t rank) {
    uint32_t d;
    asm("mapa.shared::cluster.u32 %0, %1, %2;" : "=r"(d) : "r"(addr), "r"(rank));
    return d;
}
__device__ __forceinline__ void st_async(uint32_t dst, float v, uint32_t bar) {
    asm volatile("st.async.weak.shared::cluster.mbarrier::complete_tx::bytes.f32 [%0], %1, [%2];" ::"r"(dst), "f"(v), "r"(bar) : "memory");
}
__device__ __forceinline__ void st_async2(uint32_t dst, float a, float b, uint32_t bar) {
    asm volatile("st.async.weak.shared::cluster.mbarrier::complete_tx::bytes.v2.f32 [%0], {%1, %2}, [%3];" ::"r"(dst), "f"(a), "f"(b), "r"(bar) : "memory");
}
__device__ __forceinline__ void cluster_arrive() { asm volatile("barrier.cluster.arrive.relaxed.aligned;" ::: "memory"); }
__device__ __forceinline__ void cluster_wait() { asm volatile("barrier.cluster.wait.aligned;" ::: "memory"); }
__device__ __forceinline__ void ll_ld4_if(uint4& v, const uint32_t* p, uint32_t cond) {
    asm volatile("{\n.reg .pred p;\nsetp.ne.u32 p, %5, 0;\n@p ld.relaxed.gpu.global.v4.b32 {%0,%1,%2,%3}, [%4];\n}"
                 : "+r"(v.x), "+r"(v.y), "+r"(v.z), "+r"(v.w) : "l"(p), "r"(cond) : "memory");
}
__device__ __forceinline__ float lds_f(uint32_t addr) { return __uint_as_float(lds32(addr)); }
__device__ __forceinline__ float lds_sum8(uint32_t addr) {
    float v[8];
#pragma unroll
    for (int i = 0; i < 8; i++) v[i] = lds_f(addr + i * 128);
    return ((v[0] + v[1]) + (v[2] + v[3])) + ((v[4] + v[5]) + (v[6] + v[7]));
}
__device__ __forceinline__ int tail_row(int rank, int i) {
    const int hs = (i - 2) >> 1;
    return (i < 2 ? rank * D_HEAD : D_FF + (4 * rank + ((hs & 1) << 1) + (hs >> 1)) * D_HEAD) + (i & 1) * 96;
}

struct Params {
    const __nv_bfloat16* x;
    __nv_bfloat16* out;
    const __nv_bfloat16* k;
    uint32_t* scratch;
    uint16_t step_wq2, step_wq3, step_own, step_ffn, step_tri, step_tail, pad0, pad1;
};
static_assert(sizeof(Params) == 48, "Params must fill the rest of the first parameter line");

__global__ void __cluster_dims__(CL, 1, 1) __launch_bounds__(N_THREADS, 1)
fused_decode_kernel(const Params prm, const __grid_constant__ CUtensorMap tm_wq, const __grid_constant__ CUtensorMap tm_w1,
                    const __grid_constant__ CUtensorMap tm_w3, const __grid_constant__ CUtensorMap tm_k,
                    const __grid_constant__ CUtensorMap tm_v, const __grid_constant__ CUtensorMap tm_wo,
                    const __grid_constant__ CUtensorMap tm_w2) {
    extern __shared__ uint8_t smem_raw[];
    const uint32_t sb = (smem_u32(smem_raw) + 1023u) & ~1023u;
    uint8_t* sp = smem_raw + (sb - smem_u32(smem_raw));
    const uint32_t bar = sb + SM_BAR;
    const uint32_t bar_full = bar + BAR_FULL, bar_empty = bar + BAR_EMPTY;

    const int tid = threadIdx.x;
    const int cta = blockIdx.x, cl = cta / CL, rank = cta % CL;
    const int tri = cl >= N_OWN + N_FFN;
    const int pos_k = tri ? POS_K3 : POS_K2;
    const int head_first = tri ? cl + (N_HEAD - N_CL) : 2 * cl;
    volatile uint32_t* t_first = reinterpret_cast<volatile uint32_t*>(sp + SM_T0);
    if (tid == N_CONS) {
        const __nv_bfloat16* k0 = prm.k + ((size_t)head_first * SEQ + (SEQ - WIN) + rank * 16) * D_HEAD;
#pragma unroll
        for (int u = 0; u < 2; u++) {
            mbar_init(bar_full + (pos_k + u) * 8, 1);
            asm volatile("fence.mbarrier_init.release.cluster;" ::: "memory");
            mbar_expect_tx(bar_full + (pos_k + u) * 8, TILE_BYTES);
#pragma unroll
            for (int j = 0; j < 2; j++)
                bulk_load(sb + SM_RING + (pos_k + u) * TILE_BYTES + j * PIECE_BYTES, k0 + (2 * u + j) * (CL * 16 * D_HEAD), PIECE_BYTES,
                          bar_full + (pos_k + u) * 8, stream_policy());
            if (u == 0) *t_first = now_ns();
        }
    }
    if (tid == N_CONS + 32) prefetch_tmap(&tm_wq);
    const int warp = __shfl_sync(0xffffffffu, tid >> 5, 0), lane = tid & 31;
    const bool owner = cl < N_OWN, ffn = !owner && !tri;
    const int n_heads = 2 + tri;
    const int pos_w = pos_k + n_heads * HEAD_TILES;
    const int pos_v = pos_w + (ffn ? W_TILES : 0);
    const int pos_t = pos_v + n_heads * HEAD_TILES;
    uint32_t* const g_epoch = prm.scratch;
    uint32_t* const g_x = prm.scratch + XO_H;
    const int n_start = owner ? N_THREADS : N_THREADS - 96;

    if (warp == N_CONS_WARPS) {
        if (lane == 0) {
#pragma unroll
            for (int i = 0; i < N_SLOT; i++)
                if (i != pos_k && i != pos_k + 1) mbar_init(bar_full + i * 8, 1);
            asm volatile("fence.mbarrier_init.release.cluster;" ::: "memory");
        }
        __syncwarp();
        named_arrive(6, n_start);
        cluster_arrive();
        if (lane == 0) {
            const uint64_t pol = stream_policy();
            const uint32_t t_start = *t_first;
            prefetch_tmap(&tm_k); prefetch_tmap(&tm_v);
            prefetch_tmap(owner ? &tm_w2 : &tm_w1); prefetch_tmap(owner ? &tm_wo : &tm_w3);
            uint32_t deadline = START_DELAY * 8;
            {
                const uint32_t step = tri ? prm.step_wq3 : prm.step_wq2;
#pragma unroll 1
                for (int p = 0; p < 10 + 5 * tri; p++) {
                    const uint32_t fb = bar_full + (p >> 1) * 8;
                    if (!(p & 1)) mbar_expect_tx(fb, p == 14 ? PIECE_BYTES : TILE_BYTES);
                    const int h = p < 10 ? 2 * cl + (rank >> 2) : head_first;
                    const int row = p < 10 ? (rank & 3) * 160 + p * 16 : rank * 80 + (p - 10) * 16;
                    wait_until(t_start, deadline >> 3);
                    tma_3d(sb + SM_RING + p * PIECE_BYTES, &tm_wq, 0, h * 3, row, fb, pol);
                    deadline += step;
                }
            }
            uint32_t step = owner ? prm.step_own : (tri ? prm.step_tri : prm.step_ffn);
            const int pos_end = pos_t + (owner ? TAIL_TILES : 0);
            int window = owner ? INFLIGHT : (tri ? 10 : 10);
#pragma unroll 1
            for (int pos = pos_k + 2; pos < pos_end; pos++) {
                const int slot = pos & (N_SLOT - 1);
                const uint32_t fb = bar_full + slot * 8, dst = sb + SM_RING + slot * TILE_BYTES;
                const CUtensorMap *tm0, *tm1;
                int c1 = 0, row, row_step;
                if (pos == pos_t - GATE_EARLY) mbar_arrive(bar + BAR_GO);
                if (pos >= pos_t) {
                    if (pos == pos_t) { mbar_arrive(bar + BAR_GO + 8); step = prm.step_tail; window = 10; }
                    row = tail_row(rank, pos - pos_t);
                    tm0 = tm1 = row < D_FF ? &tm_w2 : &tm_wo;
                    if (row >= D_FF) row -= D_FF;
                    c1 = cl; row_step = 48;
                } else if (pos >= pos_w && pos < pos_v) {
                    tm0 = &tm_w1; tm1 = &tm_w3;
                    c1 = cta - N_OWN * CL; row = (pos - pos_w) * 48; row_step = 0;
                } else {
                    const int u = pos - (pos < pos_w ? pos_k : pos_v), hh = u >> 4;
                    tm0 = tm1 = pos < pos_w ? &tm_k : &tm_v;
                    row = (hh == 0 ? head_first : 2 * cl + hh - tri) * SEQ + (SEQ - WIN) + rank * 16 + (u & 15) * (CL * 32);
                    row_step = CL * 16;
                }
                if (pos >= N_SLOT) mbar_wait(bar_empty + slot * 8, ((pos >> 4) - 1) & 1);
                if (pos >= window) mbar_wait(bar_full + ((pos - window) & (N_SLOT - 1)) * 8, ((pos - window) >> 4) & 1);
                mbar_expect_tx(fb, TILE_BYTES);
                wait_until(t_start, deadline >> 3);
                tma_3d(dst, tm0, 0, c1, row, fb, pol);
                deadline += step;
                wait_until(t_start, deadline >> 3);
                tma_3d(dst + PIECE_BYTES, tm1, 0, c1, row + row_step, fb, pol);
                deadline += step;
            }
        }
        return;
    }

    if (warp > N_CONS_WARPS + 2 && !owner) return;
    if (tid == N_CONS + 32) {
#pragma unroll
        for (int i = 0; i < N_SLOT; i++) mbar_init(bar_empty + i * 8, RELEASE);
        asm volatile("fence.mbarrier_init.release.cluster;" ::: "memory");
    }
    if (tid == N_CONS + 64) {
#pragma unroll
        for (int i = BAR_GO; i <= BAR_S; i += 8) mbar_init(bar + i, 1);
        mbar_expect_tx(bar + BAR_Q, (1 + tri) * CL * D_HEAD * 4);
        mbar_expect_tx(bar + BAR_ML, n_heads * CL * 8);
#pragma unroll
        for (int i = BAR_O; i <= BAR_S; i += 8) mbar_expect_tx(bar + i, 1024);
        asm volatile("fence.mbarrier_init.release.cluster;" ::: "memory");
    }
    __syncwarp();
    cluster_arrive();
    float* sst = reinterpret_cast<float*>(sp + SM_ST);
    if (warp < N_CONS_WARPS) {
        if (warp < 5) {
            const uint2 u = *reinterpret_cast<const uint2*>(prm.x + tid * 4);
            const float pivot = bf_lo(*reinterpret_cast<const uint32_t*>(prm.x));
            const float a = bf_lo(u.x) - pivot, b = bf_hi(u.x) - pivot, c = bf_lo(u.y) - pivot, d = bf_hi(u.y) - pivot;
            float s1 = (a + b) + (c + d), s2 = fmaf(a, a, fmaf(b, b, fmaf(c, c, d * d)));
#pragma unroll
            for (int o = 16; o > 0; o >>= 1) {
                s1 += __shfl_xor_sync(0xffffffffu, s1, o);
                s2 += __shfl_xor_sync(0xffffffffu, s2, o);
            }
            if (lane == 0) { sst[warp] = s1; sst[8 + warp] = s2; }
            named_sync(10, 160);
            s1 = 0.f; s2 = 0.f;
#pragma unroll
            for (int w = 0; w < 5; w++) { s1 += sst[w]; s2 += sst[8 + w]; }
            const float dm = s1 * (1.f / D_MODEL);
            const float var = fmaxf(fmaf(-dm, dm, s2 * (1.f / D_MODEL)), 0.f);
            const float mean_b = bf16r(pivot + dm);
            float den;
            asm("sqrt.approx.f32 %0, %1;" : "=f"(den) : "f"(bf16r(bf16r(var) + 1e-5f)));
            const float inv = rcp(bf16r(den));
            const uint32_t d0 = pack_bf16(bf_lo(u.x) - mean_b, bf_hi(u.x) - mean_b);
            const uint32_t d1 = pack_bf16(bf_lo(u.y) - mean_b, bf_hi(u.y) - mean_b);
            *reinterpret_cast<uint2*>(sp + SM_XN + tid * 8) =
                make_uint2(pack_bf16(bf_lo(d0) * inv, bf_hi(d0) * inv), pack_bf16(bf_lo(d1) * inv, bf_hi(d1) * inv));
        } else if (warp == 5) {
            if (lane < 8) *reinterpret_cast<uint2*>(sp + SM_XN + tid * 8) = make_uint2(0u, 0u);
        } else if (tid == 6 * 32) {
            *reinterpret_cast<uint32_t*>(sp + SM_EPOCH) = ll_ld(g_epoch);
        }
    } else if (warp == N_CONS_WARPS + 1) {
        if (rank < V_WARPS) ll_store(g_x + D_FF + (2 * cl + 1) * D_HEAD + rank * 32 + lane, 0u);
    } else if (!owner) {
        named_arrive(6, n_start);
        return;
    }
    named_sync(6, n_start);
    const uint32_t epoch = lds32(sb + SM_EPOCH);
    const uint32_t tag = 1u + (epoch & 1u);

    if (warp == N_CONS_WARPS + 1) {
        if (rank >= V_WARPS) return;
        const bool fin = owner && rank < 4;
        __nv_bfloat16* const out = prm.out + cl * 64 + rank * 16 + (lane & 15);
        float xv = 0.f;
        if (fin) xv = __bfloat162float(prm.x[cl * 64 + rank * 16 + (lane & 15)]);
        mbar_wait(bar + BAR_ML, 0);
        float wv;
        {
            const uint32_t ma = sb + SM_ML + (lane < n_heads * CL ? lane : 0) * 8;
            const float mi = lds_f(ma);
            float m = fmaxf(mi, __shfl_xor_sync(0xffffffffu, mi, 1));
            m = fmaxf(m, __shfl_xor_sync(0xffffffffu, m, 2));
            m = fmaxf(m, __shfl_xor_sync(0xffffffffu, m, 4));
            const float ei = ex2((mi - m) * LOG2E);
            float den = ei * lds_f(ma + 4);
            den += __shfl_xor_sync(0xffffffffu, den, 1);
            den += __shfl_xor_sync(0xffffffffu, den, 2);
            den += __shfl_xor_sync(0xffffffffu, den, 4);
            wv = ei * rcp(den);
        }
#pragma unroll 1
        for (int hh = 0; hh < n_heads; hh++) {
            float w[CL];
#pragma unroll
            for (int s = 0; s < CL; s++) w[s] = __shfl_sync(0xffffffffu, wv, hh * CL + s);
            uint32_t* dst = g_x + D_FF + (hh == 0 ? head_first : 2 * cl + hh - tri) * D_HEAD + rank * 32 + lane;
            const uint32_t src = sb + SM_OP + hh * 1024 + lane * 4;
            mbar_wait(bar + BAR_O + hh * 8, 0);
            float v[CL];
#pragma unroll
            for (int s = 0; s < CL; s++) v[s] = lds_f(src + s * 128);
            const float o = (fmaf(w[1], v[1], w[0] * v[0]) + fmaf(w[3], v[3], w[2] * v[2])) +
                            (fmaf(w[5], v[5], w[4] * v[4]) + fmaf(w[7], v[7], w[6] * v[6]));
            ll_store(dst, __float_as_uint(bf16r(o)) | tag);
        }
        if (fin) {
            mbar_wait(bar + BAR_G, 0);
            float f = lds_sum8(sb + SM_FG + lane * 4);
            f += __shfl_xor_sync(0xffffffffu, f, 16);
            const float g = bf16r(silu_f(bf16r(f)));
            if (cta == 0 && lane == 0) ll_store(g_epoch, epoch + 1u);
            mbar_wait(bar + BAR_S, 0);
            float s = lds_sum8(sb + SM_FS + lane * 4);
            s += __shfl_xor_sync(0xffffffffu, s, 16);
            if (lane < 16) *reinterpret_cast<uint16_t*>(out) = (uint16_t)pack_bf16(xv + bf16r(bf16r(s) * g), 0.f);
        }
        return;
    }
    if (warp >= N_CONS_WARPS + 2) {
        const int gw = warp - (N_CONS_WARPS + 2);
        static_assert(GATE_LATE <= N_SLOT - 1 - INFLIGHT, "the window does not rule out parity aliasing on the gate tile");
        mbar_wait(bar + BAR_GO, 0);
#pragma unroll 1
        for (int round = 0; round < 2; round++) {
            const int i0 = round * 4 + 2 + gw;
            const uint32_t* src0 = g_x + tail_row(rank, i0) + lane * 4;
            const uint32_t* src1 = g_x + tail_row(rank, gw & 1) + lane * 4;
            if (round == 1) {
                named_arrive(8, N_CONS + N_GATHER);
                mbar_wait(bar + BAR_GO + 8, 0);
                mbar_wait(bar_full + ((pos_t + GATE_LATE) & (N_SLOT - 1)) * 8, ((pos_t + GATE_LATE) >> 4) & 1);
            }
            uint4 v0 = make_uint4(0u, 0u, 0u, 0u), v1 = v0;
            const bool second = round == 0 && gw < 2 && lane < 24;
            uint32_t miss0 = lane < 24, miss1 = second;
            unsigned n = 0;
#pragma unroll 1
            while (true) {
                ll_ld4_if(v0, src0, miss0);
                ll_ld4_if(v1, src1, miss1);
                if (ll_bad4(v0, tag) == 0) miss0 = 0;
                if (ll_bad4(v1, tag) == 0) miss1 = 0;
                if (__all_sync(0xffffffffu, (miss0 | miss1) == 0) || ++n > SPIN_LIMIT) break;
            }
            if (lane < 24)
                *reinterpret_cast<uint2*>(sp + SM_OV + i0 * 192 + lane * 8) = make_uint2(__byte_perm(v0.x, v0.y, 0x7632), __byte_perm(v0.z, v0.w, 0x7632));
            if (second)
                *reinterpret_cast<uint2*>(sp + SM_OV + gw * 192 + lane * 8) = make_uint2(__byte_perm(v1.x, v1.y, 0x7632), __byte_perm(v1.z, v1.w, 0x7632));
        }
        named_arrive(3, N_CONS + N_GATHER);
        return;
    }


    const int q4 = lane & 3, g8 = lane >> 2;
    const int rowT = (lane & 7) + ((lane >> 4) << 3), hiT = (lane >> 3) & 1;
    const uint32_t off_v = ((3 * rowT + (warp >> 1)) * 128 + ((hiT ^ ((3 * rowT + (warp >> 1)) & 7)) << 4)) ^ ((warp & 1) << 6);

    if (warp < V_WARPS) {
#pragma unroll 1
        for (int part = 0; part <= tri; part++) {
            const uint32_t xa = sb + SM_XN + ((part ? rank * 80 - 160 : (rank & 3) * 160) + 2 * q4) * 2;
            float acc[2][4] = {};
#pragma unroll 1
            for (int p = part * 10; p < 10 + part * 5; p++) {
                const uint32_t b0 = lds32(xa + p * 32), b1 = lds32(xa + p * 32 + 16);
                mbar_wait(bar_full + (p >> 1) * 8, 0);
                uint32_t a[4];
                ldsm_x4_t(a, sb + SM_RING + p * PIECE_BYTES + off_v);
                mma_bf16(acc[0], a, b0, b1);
                ldsm_x4_t(a, sb + SM_RING + p * PIECE_BYTES + (off_v ^ 32));
                mma_bf16(acc[1], a, b0, b1);
                __syncwarp();
                if (lane == 0) mbar_arrive_n(bar_empty + (p >> 1) * 8, p == 14 ? RELEASE / V_WARPS : RELEASE / V_WARPS / 2);
            }
            if (part == 0) cluster_wait();
            const float v = pick4(acc[0][0], acc[0][2], acc[1][0], acc[1][2], q4);
            const uint32_t dst = sb + SM_QP + ((part * CL + rank) * D_HEAD + warp * 32 + q4 * 8 + g8) * 4;
#pragma unroll
            for (int d = 0; d < CL; d++) st_async(mapa(dst, d), v, mapa(bar + BAR_Q, d));
        }
        mbar_wait(bar + BAR_Q, 0);
        const float* qp = reinterpret_cast<const float*>(sp + SM_QP) + tid;
        __nv_bfloat16* qs = reinterpret_cast<__nv_bfloat16*>(sp + SM_Q) + tid;
        qs[tri * D_HEAD] = __float2bfloat16_rn((qp[0] + qp[192]) + (qp[384] + qp[576]));
        qs[(tri + 1) * D_HEAD] = __float2bfloat16_rn((qp[768] + qp[960]) + (qp[1152] + qp[1344]));
        if (tri) {
            qp += CL * D_HEAD;
            qs[0] = __float2bfloat16_rn(((qp[0] + qp[192]) + (qp[384] + qp[576])) + ((qp[768] + qp[960]) + (qp[1152] + qp[1344])));
        }
    }
    named_sync(1, N_CONS);

    {
        const int rowN = (lane & 7) + (((lane >> 3) & 1) << 3), hiN = lane >> 4;
#pragma unroll 1
        for (int hh = 0; hh < n_heads; hh++) {
            float s0 = 0.f, s1 = 0.f;
#pragma unroll 1
            for (int i = 0; i < 2; i++) {
                const int pos = pos_k + hh * HEAD_TILES + i * 8 + warp, slot = pos & (N_SLOT - 1);
                mbar_wait(bar_full + slot * 8, (pos >> 4) & 1);
                const uint32_t tb = sb + SM_RING + slot * TILE_BYTES;
                float acc[2][2][4] = {};
#pragma unroll 1
                for (int j = 0; j < 3; j++) {
                    const int swz = pos < pos_k + 2 ? 0 : (3 * rowN + j) & 7;
                    const uint32_t oj = tb + (3 * rowN + j) * 128 + ((hiN ^ swz) << 4);
                    const uint32_t qa = sb + SM_Q + (hh * D_HEAD + j * 64 + 2 * q4) * 2;
#pragma unroll
                    for (int k = 0; k < 4; k++) {
                        const uint32_t b0 = lds32(qa + k * 32), b1 = lds32(qa + k * 32 + 16);
                        uint32_t a[4];
                        ldsm_x4(a, oj ^ (k << 5));
                        mma_bf16(acc[0][k & 1], a, b0, b1);
                        ldsm_x4(a, (oj + PIECE_BYTES) ^ (k << 5));
                        mma_bf16(acc[1][k & 1], a, b0, b1);
                    }
                }
                __syncwarp();
                if (lane == 0) mbar_arrive_n(bar_empty + slot * 8, RELEASE);
                const float raw = pick4(acc[0][0][0] + acc[0][1][0], acc[0][0][2] + acc[0][1][2],
                                        acc[1][0][0] + acc[1][1][0], acc[1][0][2] + acc[1][1][2], q4);
                s0 = s1;
                s1 = bf16r(bf16r(raw) * 0.07216878364870323f);
            }
            float m = fmaxf(s0, s1);
#pragma unroll
            for (int o = 16; o > 0; o >>= 1) m = fmaxf(m, __shfl_xor_sync(0xffffffffu, m, o));
            if (lane == 0) sst[hh * 8 + warp] = m;
            named_sync(1, N_CONS);
#pragma unroll
            for (int w = 0; w < 8; w++) m = fmaxf(m, sst[hh * 8 + w]);
            const float p0 = ex2((s0 - m) * LOG2E), p1 = ex2((s1 - m) * LOG2E);
            float l = p0 + p1;
#pragma unroll
            for (int o = 16; o > 0; o >>= 1) l += __shfl_xor_sync(0xffffffffu, l, o);
            if (lane == 0) sst[24 + hh * 8 + warp] = l;
            __nv_bfloat16* ps = reinterpret_cast<__nv_bfloat16*>(sp + SM_P) + hh * 512 + warp * 32 + q4 * 8 + g8;
            ps[0] = __float2bfloat16_rn(p0);
            ps[256] = __float2bfloat16_rn(p1);
        }
        named_sync(1, N_CONS);
        if (warp == 7 && lane < n_heads * CL && (lane & 7) < V_WARPS) {
            const float* st = sst + (lane & 24);
            float m = st[0], l = st[24];
#pragma unroll
            for (int w = 1; w < 8; w++) { m = fmaxf(m, st[w]); l += st[24 + w]; }
            st_async2(mapa(sb + SM_ML + ((lane & 24) + rank) * 8, lane & 7), m, l, mapa(bar + BAR_ML, lane & 7));
        }
    }

    const uint32_t off_w = (warp >> 2) * PIECE_BYTES + rowT * 128 + (((((warp & 3) << 1) | hiT) ^ (rowT & 7)) << 4);

    if (ffn) {
        float acc[3][4] = {};
#pragma unroll 1
        for (int i = 0; i < W_TILES; i++) {
            const int pos = pos_w + i, slot = pos & (N_SLOT - 1);
            const uint32_t xa = sb + SM_XN + (i * 48 + 2 * q4) * 2;
            mbar_wait(bar_full + slot * 8, (pos >> 4) & 1);
#pragma unroll
            for (int k = 0; k < 3; k++) {
                uint32_t a[4];
                ldsm_x4_t(a, sb + SM_RING + slot * TILE_BYTES + off_w + k * 2048);
                mma_bf16(acc[k], a, lds32(xa + k * 32), lds32(xa + k * 32 + 16));
            }
            __syncwarp();
            if (lane == 0) mbar_arrive_n(bar_empty + slot * 8, RELEASE / N_CONS_WARPS);
        }
        const float v = bf16r((q4 & 1) ? (acc[0][2] + acc[1][2]) + acc[2][2] : (acc[0][0] + acc[1][0]) + acc[2][0]);
        const int col = (warp & 3) * 16 + (q4 & 1) * 8 + g8;
        if (warp >= 4 && q4 < 2) sst[64 + col] = v;
        named_sync(1, N_CONS);
        if (warp < 4 && q4 < 2)
            ll_store(g_x + (cta - N_OWN * CL) * 64 + col, __float_as_uint(bf16r(bf16r(silu_f(v)) * sst[64 + col])) | tag);
    }

    if (warp < V_WARPS) {
        const uint32_t rdst = mapa(sb + SM_OP + rank * 128 + (q4 * 8 + g8) * 4, warp), rbar = mapa(bar + BAR_O, warp);
#pragma unroll 1
        for (int hh = 0; hh < n_heads; hh++) {
            float oacc[2][2][4] = {};
#pragma unroll 2
            for (int u = hh * HEAD_TILES; u < (hh + 1) * HEAD_TILES; u++) {
                const int pos = pos_v + u, slot = pos & (N_SLOT - 1);
                uint32_t ta = sb + SM_RING + slot * TILE_BYTES + off_v, tc = ta ^ 32;
                asm volatile("" : "+r"(ta), "+r"(tc));
                const uint32_t pa = sb + SM_P + (u * 32 + 2 * q4) * 2;
                const uint32_t b0 = lds32(pa), b1 = lds32(pa + 16), b2 = lds32(pa + 32), b3 = lds32(pa + 48);
                mbar_wait(bar_full + slot * 8, (pos >> 4) & 1);
                uint32_t a[4][4];
                ldsm_x4_t(a[0], ta);
                ldsm_x4_t(a[1], tc);
                ldsm_x4_t(a[2], ta + PIECE_BYTES);
                ldsm_x4_t(a[3], tc + PIECE_BYTES);
                mma_bf16(oacc[0][0], a[0], b0, b1);
                mma_bf16(oacc[1][0], a[1], b0, b1);
                mma_bf16(oacc[0][1], a[2], b2, b3);
                mma_bf16(oacc[1][1], a[3], b2, b3);
                __syncwarp();
                if (lane == 0) mbar_arrive_n(bar_empty + slot * 8, RELEASE / V_WARPS);
            }
            const float v = pick4(oacc[0][0][0] + oacc[0][1][0], oacc[0][0][2] + oacc[0][1][2],
                                  oacc[1][0][0] + oacc[1][1][0], oacc[1][0][2] + oacc[1][1][2], q4);
            st_async(rdst + hh * 1024, v, rbar + hh * 8);
        }
    }
    if (!owner) return;

    {
        constexpr int P0 = POS_K2 + 4 * HEAD_TILES;
        const uint32_t rdst = mapa(sb + SM_FG + (rank * 2 + (warp >> 2)) * 64 + ((q4 & 1) * 8 + g8) * 4, warp & 3);
        const uint32_t rbar = mapa(bar + BAR_G, warp & 3);
        const uint32_t va = sb + SM_OV + ((warp >> 2) * 48 + 2 * q4) * 2;
        named_sync(8, N_CONS + N_GATHER);
        float acc[3][4] = {};
#pragma unroll 1
        for (int i = 0; i < 6; i++) {
            const int slot = (P0 + i) & (N_SLOT - 1);
            uint32_t b[3][2];
#pragma unroll
            for (int k = 0; k < 3; k++) { b[k][0] = lds32(va + i * 192 + k * 32); b[k][1] = lds32(va + i * 192 + k * 32 + 16); }
            mbar_wait(bar_full + slot * 8, ((P0 + i) >> 4) & 1);
#pragma unroll
            for (int k = 0; k < 3; k++) {
                uint32_t a[4];
                ldsm_x4_t(a, sb + SM_RING + slot * TILE_BYTES + off_w + k * 2048);
                mma_bf16(acc[k], a, b[k][0], b[k][1]);
            }
            if (i == 1) {
                if (q4 < 2) st_async(rdst, q4 ? (acc[0][2] + acc[1][2]) + acc[2][2] : (acc[0][0] + acc[1][0]) + acc[2][0], rbar);
#pragma unroll
                for (int k = 0; k < 3; k++) acc[k][0] = acc[k][1] = acc[k][2] = acc[k][3] = 0.f;
            }
        }
        uint32_t ae[LATE_EARLY + 1][3][4];
#pragma unroll
        for (int i = 0; i < LATE_EARLY; i++) {
            const int slot = (P0 + 6 + i) & (N_SLOT - 1);
            mbar_wait(bar_full + slot * 8, ((P0 + 6 + i) >> 4) & 1);
#pragma unroll
            for (int k = 0; k < 3; k++) ldsm_x4_t(ae[i][k], sb + SM_RING + slot * TILE_BYTES + off_w + k * 2048);
        }
        named_sync(3, N_CONS + N_GATHER);
        uint32_t b[4][3][2];
#pragma unroll
        for (int i = 0; i < 4; i++)
#pragma unroll
            for (int k = 0; k < 3; k++) { b[i][k][0] = lds32(va + (6 + i) * 192 + k * 32); b[i][k][1] = lds32(va + (6 + i) * 192 + k * 32 + 16); }
#pragma unroll
        for (int i = 0; i < LATE_EARLY; i++)
#pragma unroll
            for (int k = 0; k < 3; k++) mma_bf16(acc[k], ae[i][k], b[i][k][0], b[i][k][1]);
#pragma unroll
        for (int i = LATE_EARLY; i < 4; i++) {
            const int slot = (P0 + 6 + i) & (N_SLOT - 1);
            mbar_wait(bar_full + slot * 8, ((P0 + 6 + i) >> 4) & 1);
            uint32_t a[3][4];
#pragma unroll
            for (int k = 0; k < 3; k++) ldsm_x4_t(a[k], sb + SM_RING + slot * TILE_BYTES + off_w + k * 2048);
#pragma unroll
            for (int k = 0; k < 3; k++) mma_bf16(acc[k], a[k], b[i][k][0], b[i][k][1]);
        }
        if (q4 < 2) st_async(rdst + (SM_FS - SM_FG), q4 ? (acc[0][2] + acc[1][2]) + acc[2][2] : (acc[0][0] + acc[1][0]) + acc[2][0], rbar + (BAR_S - BAR_G));
    }
}

typedef CUresult (*EncodeTiledFn)(CUtensorMap*, CUtensorMapDataType, cuuint32_t, void*, const cuuint64_t*,
                                  const cuuint64_t*, const cuuint32_t*, const cuuint32_t*, CUtensorMapInterleave,
                                  CUtensorMapSwizzle, CUtensorMapL2promotion, CUtensorMapFloatOOBfill);

void encode_map(EncodeTiledFn fn, CUtensorMap* m, const void* base, cuuint64_t rows, cuuint64_t cols, cuuint32_t b1, cuuint32_t b2) {
    const cuuint64_t dims[3] = {64, cols / 64, rows};
    const cuuint64_t strides[2] = {128, cols * 2};
    const cuuint32_t box[3] = {64, b1, b2};
    const cuuint32_t estr[3] = {1, 1, 1};
    fn(m, CU_TENSOR_MAP_DATA_TYPE_BFLOAT16, 3, const_cast<void*>(base), dims, strides, box, estr,
       CU_TENSOR_MAP_INTERLEAVE_NONE, CU_TENSOR_MAP_SWIZZLE_128B, CU_TENSOR_MAP_L2_PROMOTION_NONE,
       CU_TENSOR_MAP_FLOAT_OOB_FILL_NONE);
}

}

extern "C" void kernel_launch(void* const* d_in, const int* in_sizes, int n_in, void* d_out, int out_size) {
    (void)in_sizes; (void)n_in; (void)out_size;
    static EncodeTiledFn encode = nullptr;
    static double pace_scale = 1.0;
    static void* scratch = nullptr;
    if (!encode) {
        int dev = 0, mem_khz = 0, bus_bits = 0;
        cudaGetDevice(&dev);
        cudaDeviceGetAttribute(&mem_khz, cudaDevAttrMemoryClockRate, dev);
        cudaDeviceGetAttribute(&bus_bits, cudaDevAttrGlobalMemoryBusWidth, dev);
        const double peak_gbs = 2.0 * mem_khz * 1e-6 * bus_bits / 8.0;
        if (peak_gbs > 0.0) pace_scale = PACE_REF_GBS / peak_gbs;
        void* fn = nullptr;
        cudaDriverEntryPointQueryResult qr;
        cudaGetDriverEntryPoint("cuTensorMapEncodeTiled", &fn, cudaEnableDefault, &qr);
        encode = reinterpret_cast<EncodeTiledFn>(fn);
        cudaFuncSetAttribute(fused_decode_kernel, cudaFuncAttributeMaxDynamicSharedMemorySize, SM_ALLOC);
        cudaGetSymbolAddress(&scratch, g_scratch);
    }
    CUtensorMap tm_k, tm_v, tm_wq, tm_w1, tm_w3, tm_wo, tm_w2;
    encode_map(encode, &tm_k, d_in[1], (cuuint64_t)N_HEAD * SEQ, D_HEAD, 3, 16);
    encode_map(encode, &tm_v, d_in[2], (cuuint64_t)N_HEAD * SEQ, D_HEAD, 3, 16);
    encode_map(encode, &tm_wq, d_in[3], D_MODEL, N_HEAD * D_HEAD, 3, 16);
    encode_map(encode, &tm_w1, d_in[6], D_MODEL, D_FF, 1, 48);
    encode_map(encode, &tm_w3, d_in[7], D_MODEL, D_FF, 1, 48);
    encode_map(encode, &tm_wo, d_in[4], N_HEAD * D_HEAD, D_MODEL, 1, 48);
    encode_map(encode, &tm_w2, d_in[8], D_FF, D_MODEL, 1, 48);
    Params prm;
    prm.x = static_cast<const __nv_bfloat16*>(d_in[0]);
    prm.out = static_cast<__nv_bfloat16*>(d_out);
    prm.k = static_cast<const __nv_bfloat16*>(d_in[1]);
    prm.scratch = static_cast<uint32_t*>(scratch);
    auto step = [&](double pace, double bytes, int pieces) { return (uint16_t)(8.0 * pace * pace_scale * bytes / (128.0 * TILE_BYTES) / pieces); };
    const double b_wq = 2.0 * D_MODEL * N_HEAD * D_HEAD;
    const double b_mid = 4.0 * N_HEAD * WIN * D_HEAD - 2.0 * N_CTA * TILE_BYTES + 4.0 * D_MODEL * D_FF;
    const double b_tail = 2.0 * D_MODEL * (D_FF + N_HEAD * D_HEAD);
    prm.step_wq2 = step(PACE_HEAD, b_wq, 10);
    prm.step_wq3 = step(PACE_HEAD, b_wq, 15);
    prm.step_own = step(PACE_MID, b_mid, 2 * (4 * HEAD_TILES - 2));
    prm.step_ffn = step(PACE_MID, b_mid, 2 * (4 * HEAD_TILES - 2 + W_TILES));
    prm.step_tri = step(PACE_MID, b_mid, 2 * (6 * HEAD_TILES - 2));
    prm.step_tail = step(PACE_TAIL, b_tail, 2 * TAIL_TILES);
    prm.pad0 = prm.pad1 = 0;
    fused_decode_kernel<<<N_CTA, N_THREADS, SM_ALLOC, cudaStreamPerThread>>>(prm, tm_wq, tm_w1, tm_w3, tm_k, tm_v, tm_wo, tm_w2);
}
```

```cpp
#include <cuda_runtime.h>
#include <cuda_bf16.h>
#include <cuda.h>
#include <stdint.h>

namespace {

constexpr int D_MODEL = 640;
constexpr int N_HEAD = 32;
constexpr int D_HEAD = 192;
constexpr int SEQ = 32768;
constexpr int WIN = 4096;
constexpr int D_FF = 1536;

constexpr int CL = 8;
constexpr int N_CL = 15;
constexpr int N_CTA = CL * N_CL;
constexpr int N_OWN = 10;
constexpr int N_FFN = 3;
constexpr int TILE_BYTES = 12288;
constexpr int PIECE_BYTES = TILE_BYTES / 2;
constexpr int N_SLOT = 16;
constexpr int HEAD_TILES = WIN / CL / 32;
constexpr int W_TILES = 14;
constexpr int TAIL_TILES = 10;
constexpr int POS_WQ = 2, POS_K2 = 5, POS_K3 = 8;

constexpr int N_CONS_WARPS = 8;
constexpr int N_CONS = N_CONS_WARPS * 32;
constexpr int N_GATHER = 128;
constexpr int N_THREADS = N_CONS + 64 + N_GATHER;
constexpr int V_WARPS = 6;
constexpr int RELEASE = 24;

constexpr double PACE_HEAD = 490, PACE_MID = 479, PACE_LATE = 495, PACE_TAIL = 478, PACE_REF_GBS = 3352.32;
constexpr int START_DELAY = 200;
constexpr int GATE_EARLY = 4;
constexpr int LATE_EARLY = 2;
constexpr int GATE_LATE = 3;

constexpr unsigned SPIN_LIMIT = 1u << 22;

constexpr int SM_RING = 0;
constexpr int SM_BAR = N_SLOT * TILE_BYTES;
constexpr int BAR_FULL = 0, BAR_EMPTY = 128, BAR_GO = 256, BAR_Q = 272, BAR_ML = 280, BAR_O = 288, BAR_G = 312, BAR_S = 320, BAR_X = 328;
constexpr int SM_T0 = SM_BAR + 448, SM_EPOCH = SM_BAR + 452;
constexpr int SM_XN = SM_BAR + 512;
constexpr int SM_Q = SM_XN + 1408;
constexpr int SM_ST = SM_Q + 1152;
constexpr int SM_ML = SM_ST + 512;
constexpr int SM_P = SM_ML + 256;
constexpr int SM_QP = SM_P + 3072;
constexpr int SM_OP = SM_QP + 12288;
constexpr int SM_OV = SM_OP + 3072;
constexpr int SM_FG = SM_OV + 1920;
constexpr int SM_FS = SM_FG + 1024;
constexpr int SM_ALLOC = SM_FS + 1024 + 1024;

constexpr int XO_H = 32;
constexpr int XO_END = XO_H + D_FF + N_HEAD * D_HEAD;
__device__ __align__(128) uint32_t g_scratch[XO_END];

__device__ __forceinline__ uint32_t smem_u32(const void* p) { return (uint32_t)__cvta_generic_to_shared(p); }

__device__ __forceinline__ void mbar_init(uint32_t bar, uint32_t cnt) {
    asm volatile("mbarrier.init.shared::cta.b64 [%0], %1;" ::"r"(bar), "r"(cnt) : "memory");
}
__device__ __forceinline__ void mbar_expect_tx(uint32_t bar, uint32_t bytes) {
    asm volatile("mbarrier.arrive.expect_tx.shared::cta.b64 _, [%0], %1;" ::"r"(bar), "r"(bytes) : "memory");
}
__device__ __forceinline__ void mbar_arrive(uint32_t bar) {
    asm volatile("mbarrier.arrive.shared::cta.b64 _, [%0];" ::"r"(bar) : "memory");
}
__device__ __forceinline__ void mbar_wait(uint32_t bar, uint32_t parity) {
    asm volatile(
        "{\n.reg .pred p, q;\n.reg .u32 n;\n"
        "mov.u32 n, 0;\n"
        "WAIT_LOOP:\n"
        "add.u32 n, n, 1;\n"
        "setp.lt.u32 q, n, %2;\n"
        "mbarrier.try_wait.parity.shared::cta.b64 p, [%0], %1;\n"
        "and.pred q, q, !p;\n"
        "@q bra WAIT_LOOP;\n}"
        ::"r"(bar), "r"(parity), "n"(SPIN_LIMIT) : "memory");
}
__device__ __forceinline__ void named_sync(int id, int n) {
    asm volatile("bar.sync %0, %1;" ::"r"(id), "r"(n) : "memory");
}
__device__ __forceinline__ void named_arrive(int id, int n) {
    asm volatile("bar.arrive %0, %1;" ::"r"(id), "r"(n) : "memory");
}
__device__ __forceinline__ uint64_t stream_policy() {
    uint64_t pol;
    asm volatile("createpolicy.fractional.L2::evict_first.b64 %0, 1.0;" : "=l"(pol));
    return pol;
}
__device__ __forceinline__ void bulk_load(uint32_t dst, const void* src, uint32_t bytes, uint32_t bar, uint64_t pol) {
    asm volatile("cp.async.bulk.shared::cluster.global.mbarrier::complete_tx::bytes.L2::cache_hint [%0], [%1], %2, [%3], %4;"
                 ::"r"(dst), "l"(src), "r"(bytes), "r"(bar), "l"(pol) : "memory");
}
__device__ __forceinline__ void tma_3d(uint32_t dst, const CUtensorMap* tm, int c0, int c1, int c2, uint32_t bar, uint64_t pol) {
    asm volatile("cp.async.bulk.tensor.3d.shared::cluster.global.mbarrier::complete_tx::bytes.L2::cache_hint [%0], [%1, {%3, %4, %5}], [%2], %6;"
                 ::"r"(dst), "l"(tm), "r"(bar), "r"(c0), "r"(c1), "r"(c2), "l"(pol) : "memory");
}
__device__ __forceinline__ void prefetch_tmap(const CUtensorMap* tm) {
    asm volatile("prefetch.tensormap [%0];" ::"l"(tm) : "memory");
}
__device__ __forceinline__ void ldsm_x4(uint32_t (&r)[4], uint32_t addr) {
    asm volatile("ldmatrix.sync.aligned.m8n8.x4.shared.b16 {%0,%1,%2,%3}, [%4];"
                 : "=r"(r[0]), "=r"(r[1]), "=r"(r[2]), "=r"(r[3]) : "r"(addr) : "memory");
}
__device__ __forceinline__ void ldsm_x4_t(uint32_t (&r)[4], uint32_t addr) {
    asm volatile("ldmatrix.sync.aligned.m8n8.x4.trans.shared.b16 {%0,%1,%2,%3}, [%4];"
                 : "=r"(r[0]), "=r"(r[1]), "=r"(r[2]), "=r"(r[3]) : "r"(addr) : "memory");
}
__device__ __forceinline__ void mma_bf16(float (&c)[4], const uint32_t (&a)[4], uint32_t b0, uint32_t b1) {
    asm volatile("mma.sync.aligned.m16n8k16.row.col.f32.bf16.bf16.f32 {%0,%1,%2,%3}, {%4,%5,%6,%7}, {%8,%9}, {%0,%1,%2,%3};"
                 : "+f"(c[0]), "+f"(c[1]), "+f"(c[2]), "+f"(c[3])
                 : "r"(a[0]), "r"(a[1]), "r"(a[2]), "r"(a[3]), "r"(b0), "r"(b1));
}
__device__ __forceinline__ float bf16r(float v) {
    uint32_t p;
    asm("cvt.rn.bf16x2.f32 %0, %1, %2;" : "=r"(p) : "f"(v), "f"(0.f));
    return __uint_as_float(p);
}
__device__ __forceinline__ uint32_t lds32(uint32_t addr) {
    uint32_t v;
    asm volatile("ld.shared.b32 %0, [%1];" : "=r"(v) : "r"(addr) : "memory");
    return v;
}
__device__ __forceinline__ float bf_lo(uint32_t v) { return __uint_as_float(v << 16); }
__device__ __forceinline__ float bf_hi(uint32_t v) { return __uint_as_float(v & 0xffff0000u); }
__device__ __forceinline__ uint32_t pack_bf16(float lo, float hi) {
    const __nv_bfloat162 p = __floats2bfloat162_rn(lo, hi);
    return *reinterpret_cast<const uint32_t*>(&p);
}
__device__ __forceinline__ uint32_t now_ns() {
    unsigned long long t;
    asm volatile("mov.u64 %0, %%globaltimer;" : "=l"(t));
    return (uint32_t)t;
}

__device__ __forceinline__ void wait_until(uint32_t t_start, uint32_t deadline) {
    unsigned n = 0;
    while (now_ns() - t_start < deadline && ++n < SPIN_LIMIT) {}
}

__device__ __forceinline__ uint32_t ll_bad4(const uint4& v, uint32_t tag) {
    uint32_t lo, hi;
    asm("lop3.b32 %0, %1, %2, %3, 0x7E;" : "=r"(lo) : "r"(v.x), "r"(v.y), "r"(tag));
    asm("lop3.b32 %0, %1, %2, %3, 0x7E;" : "=r"(hi) : "r"(v.z), "r"(v.w), "r"(tag));
    return (lo | hi) & 3u;
}
__device__ __forceinline__ float ex2(float v) {
    float r;
    asm("ex2.approx.ftz.f32 %0, %1;" : "=f"(r) : "f"(v));
    return r;
}
__device__ __forceinline__ float rcp(float v) {
    float r;
    asm("rcp.approx.ftz.f32 %0, %1;" : "=f"(r) : "f"(v));
    return r;
}
constexpr float LOG2E = 1.4426950408889634f;
__device__ __forceinline__ void ll_store(uint32_t* p, uint32_t w) {
    asm volatile("st.relaxed.gpu.global.b32 [%0], %1;" ::"l"(p), "r"(w) : "memory");
}
__device__ __forceinline__ uint32_t ll_ld(const uint32_t* p) {
    uint32_t v;
    asm volatile("ld.relaxed.gpu.global.b32 %0, [%1];" : "=r"(v) : "l"(p) : "memory");
    return v;
}
__device__ __forceinline__ float pick4(float a, float b, float c, float d, int j) {
    const float lo = (j & 1) ? b : a, hi = (j & 1) ? d : c;
    return (j & 2) ? hi : lo;
}
__device__ __forceinline__ float silu_f(float v) { return v * rcp(1.f + ex2(-LOG2E * v)); }

__device__ __forceinline__ void mbar_arrive_n(uint32_t bar, uint32_t n) {
    asm volatile("mbarrier.arrive.shared::cta.b64 _, [%0], %1;" ::"r"(bar), "r"(n) : "memory");
}
__device__ __forceinline__ uint32_t mapa(uint32_t addr, uint32_t rank) {
    uint32_t d;
    asm("mapa.shared::cluster.u32 %0, %1, %2;" : "=r"(d) : "r"(addr), "r"(rank));
    return d;
}
__device__ __forceinline__ void st_async(uint32_t dst, float v, uint32_t bar) {
    asm volatile("st.async.weak.shared::cluster.mbarrier::complete_tx::bytes.f32 [%0], %1, [%2];" ::"r"(dst), "f"(v), "r"(bar) : "memory");
}
__device__ __forceinline__ void st_async2(uint32_t dst, float a, float b, uint32_t bar) {
    asm volatile("st.async.weak.shared::cluster.mbarrier::complete_tx::bytes.v2.f32 [%0], {%1, %2}, [%3];" ::"r"(dst), "f"(a), "f"(b), "r"(bar) : "memory");
}
__device__ __forceinline__ void cluster_arrive() { asm volatile("barrier.cluster.arrive.relaxed.aligned;" ::: "memory"); }
__device__ __forceinline__ void cluster_wait() { asm volatile("barrier.cluster.wait.aligned;" ::: "memory"); }
__device__ __forceinline__ void ll_ld4_if(uint4& v, const uint32_t* p, uint32_t cond) {
    asm volatile("{\n.reg .pred p;\nsetp.ne.u32 p, %5, 0;\n@p ld.relaxed.gpu.global.v4.b32 {%0,%1,%2,%3}, [%4];\n}"
                 : "+r"(v.x), "+r"(v.y), "+r"(v.z), "+r"(v.w) : "l"(p), "r"(cond) : "memory");
}
__device__ __forceinline__ float lds_f(uint32_t addr) { return __uint_as_float(lds32(addr)); }
__device__ __forceinline__ float lds_colsum(uint32_t addr) {
    float v[8];
#pragma unroll
    for (int i = 0; i < 8; i++) v[i] = lds_f(addr + i * 128);
    const float s = ((v[0] + v[1]) + (v[2] + v[3])) + ((v[4] + v[5]) + (v[6] + v[7]));
    return s + __shfl_xor_sync(0xffffffffu, s, 16);
}

constexpr uint32_t FIRST_MUL = 257, FIRST_MASK = 0x7807;
__device__ __forceinline__ int pair_head(int cl, int j) {
    return 2 * cl + j;
}
__device__ __forceinline__ int third_head(int cl) {
    return cl + (N_HEAD - N_CL);
}
__device__ __forceinline__ int head_at(int cl, int hh, int tri) { return (hh & tri) ? third_head(cl) : pair_head(cl, hh >> tri); }
__device__ __forceinline__ int tail_row(int rank, int i) {
    if (i < 2) return i * 768 + rank * 96;
    const int j = 4 * (i - 2) + (rank >> 1), q = rank & 1;
    return D_FF + (2 * (j & 15) + (j >> 4)) * D_HEAD + q * 96;
}

struct Params {
    const __nv_bfloat16* x;
    __nv_bfloat16* out;
    const __nv_bfloat16* k;
    uint32_t* scratch;
    uint16_t step_wq2, step_wq3, step_own, step_ffn, step_tri, step_tail, late, pad;
};
static_assert(sizeof(Params) == 48, "Params must fill the rest of the first parameter line");

__global__ void __cluster_dims__(CL, 1, 1) __launch_bounds__(N_THREADS, 1)
fused_decode_kernel(const Params prm, const __grid_constant__ CUtensorMap tm_wq, const __grid_constant__ CUtensorMap tm_w1,
                    const __grid_constant__ CUtensorMap tm_w3, const __grid_constant__ CUtensorMap tm_k,
                    const __grid_constant__ CUtensorMap tm_v, const __grid_constant__ CUtensorMap tm_wo,
                    const __grid_constant__ CUtensorMap tm_w2) {
    extern __shared__ uint8_t smem_raw[];
    asm volatile("{\n.reg .pred p;\nsetp.lt.u32 p, %1, %2;\n@p prefetch.global.L2 [%0];\n}"
                 ::"l"(reinterpret_cast<const char*>(prm.k) + (size_t)(((blockIdx.x * FIRST_MUL) & FIRST_MASK) * (TILE_BYTES / 32) + threadIdx.x) * 32),
                   "r"(threadIdx.x), "n"(TILE_BYTES / 32) : "memory");
    const uint32_t sb = (smem_u32(smem_raw) + 1023u) & ~1023u;
    uint8_t* sp = smem_raw + (sb - smem_u32(smem_raw));
    const uint32_t bar = sb + SM_BAR;
    const uint32_t bar_full = bar + BAR_FULL, bar_empty = bar + BAR_EMPTY;

    const int tid = threadIdx.x;
    const int cta = blockIdx.x, cl = blockIdx.x / CL, rank = blockIdx.x % CL;
    const int tri = cl >= N_OWN + N_FFN;
    const int pos_k = tri ? POS_K3 : POS_K2;
    volatile uint32_t* t_first = reinterpret_cast<volatile uint32_t*>(sp + SM_T0);
    if (tid == N_CONS) {
        const __nv_bfloat16* k0 = prm.k + (uint32_t)(pair_head(cl, 0) * SEQ + rank * 32) * (size_t)D_HEAD;
#pragma unroll
        for (int u = 0; u < 2; u++) {
            mbar_init(bar_full + u * 8, 1);
            asm volatile("fence.mbarrier_init.release.cluster;" ::: "memory");
            mbar_expect_tx(bar_full + u * 8, TILE_BYTES);
            bulk_load(sb + SM_RING + u * TILE_BYTES, k0 + u * (CL * 32 * D_HEAD), TILE_BYTES, bar_full + u * 8, stream_policy());
            if (u == 0) *t_first = now_ns();
        }
    }
    if (tid == N_CONS + 32) prefetch_tmap(&tm_wq);
    const int warp = __shfl_sync(0xffffffffu, tid >> 5, 0), lane = tid & 31;
    const bool owner = cl < N_OWN, ffn = !owner && !tri;
    const int n_heads = 2 + tri;
    const int pos_w = pos_k + n_heads * HEAD_TILES;
    const int pos_v = pos_w + (ffn ? W_TILES : 0);
    const int pos_t = pos_v + n_heads * HEAD_TILES;
    uint32_t* const g_epoch = prm.scratch;
    uint32_t* const g_x = prm.scratch + XO_H;
    const int n_start = owner ? N_THREADS : N_THREADS - 96;

    if (warp == N_CONS_WARPS) {
        if (lane == 0) {
#pragma unroll
            for (int i = 2; i < N_SLOT; i++) mbar_init(bar_full + i * 8, 1);
            asm volatile("fence.mbarrier_init.release.cluster;" ::: "memory");
        }
        __syncwarp();
        named_arrive(6, n_start);
        cluster_arrive();
        if (lane == 0) {
            const uint64_t pol = stream_policy();
            const uint32_t t_start = *t_first;
            uint32_t deadline = START_DELAY * 8;
            {
                const uint32_t step = tri ? prm.step_wq3 : prm.step_wq2;
#pragma unroll 1
                for (int p = 0; p < 10 + 5 * tri; p++) {
                    const uint32_t fb = bar_full + (POS_WQ + (p >> 1)) * 8;
                    if (!(p & 1)) mbar_expect_tx(fb, p == 14 ? PIECE_BYTES : TILE_BYTES);
                    const int h = p < 10 ? pair_head(cl, rank >> 2) : third_head(cl);
                    const int row = p < 10 ? p * 64 + (rank & 3) * 16 : (p - 10) * 128 + rank * 16;
                    wait_until(t_start, deadline >> 3);
                    tma_3d(sb + SM_RING + POS_WQ * TILE_BYTES + p * PIECE_BYTES, &tm_wq, 0, h * 3, row, fb, pol);
                    deadline += step;
                }
            }
            uint32_t step = owner ? prm.step_own : (tri ? prm.step_tri : prm.step_ffn);
            const int pos_end = pos_t + (owner ? TAIL_TILES : 0);
            const int pos_late = pos_t - (owner ? 16 : (tri ? 24 : 20));
#pragma unroll 1
            for (int pos = pos_k + 2; pos < pos_end; pos++) {
                const int slot = pos & (N_SLOT - 1);
                const CUtensorMap* tm;
                int c1 = 0, row;
                if (pos >= pos_t) {
                    step = prm.step_tail;
                    row = tail_row(rank, pos - pos_t);
                    tm = row < D_FF ? &tm_w2 : &tm_wo;
                    if (row >= D_FF) row -= D_FF;
                    c1 = cl;
                } else if (pos >= pos_w && pos < pos_v) {
                    const bool up = pos >= pos_w + W_TILES / 2;
                    tm = up ? &tm_w3 : &tm_w1;
                    c1 = cta - N_OWN * CL;
                    row = (pos - pos_w - (up ? W_TILES / 2 : 0)) * 96;
                } else {
                    const int u = pos - (pos < pos_w ? pos_k : pos_v), hh = u >> 4;
                    tm = pos < pos_w ? &tm_k : &tm_v;
                    row = head_at(cl, hh, tri) * SEQ + (SEQ - WIN) + rank * 32 + (u & 15) * (CL * 32);
                }
                if (pos >= N_SLOT) mbar_wait(bar_empty + slot * 8, ((pos >> 4) - 1) & 1);
                mbar_expect_tx(bar_full + slot * 8, TILE_BYTES);
                wait_until(t_start, deadline >> 3);
                tma_3d(sb + SM_RING + slot * TILE_BYTES, tm, 0, c1, row, bar_full + slot * 8, pol);
                deadline += step;
                if (pos == pos_late) step = step * prm.late >> 12;
                if (pos == pos_t - GATE_EARLY) mbar_arrive(bar + BAR_GO);
                if (pos == pos_t + GATE_LATE) mbar_arrive(bar + BAR_GO + 8);
            }
        }
        return;
    }

    if (warp > N_CONS_WARPS + 2 && !owner) return;
    if (tid == N_CONS + 32) {
#pragma unroll
        for (int i = 0; i < N_SLOT; i++) mbar_init(bar_empty + i * 8, RELEASE);
        asm volatile("fence.mbarrier_init.release.cluster;" ::: "memory");
    }
    if (tid == N_CONS + 64) {
#pragma unroll
        for (int i = BAR_GO; i <= BAR_X; i += 8) mbar_init(bar + i, 1);
        mbar_expect_tx(bar + BAR_X, D_MODEL * 2 + 4);
        mbar_expect_tx(bar + BAR_Q, (1 + tri) * CL * D_HEAD * 4);
        mbar_expect_tx(bar + BAR_ML, n_heads * CL * 8);
#pragma unroll
        for (int i = BAR_O; i <= BAR_S; i += 8) mbar_expect_tx(bar + i, 1024);
        asm volatile("fence.mbarrier_init.release.cluster;" ::: "memory");
    }
    __syncwarp();
    cluster_arrive();
    float* sst = reinterpret_cast<float*>(sp + SM_ST);
    if (tid < 8) *reinterpret_cast<uint2*>(sp + SM_XN + D_MODEL * 2 + tid * 8) = make_uint2(0u, 0u);
    if (rank == CL - 1 && warp >= V_WARPS && warp < N_CONS_WARPS) {
        if (warp == V_WARPS) {
            const uint32_t ep = ll_ld(g_epoch);
            cluster_wait();
            if (lane < CL) st_async(mapa(sb + SM_EPOCH, lane), __uint_as_float(ep), mapa(bar + BAR_X, lane));
        } else {
            uint2 u[5];
#pragma unroll
            for (int i = 0; i < 5; i++) u[i] = *reinterpret_cast<const uint2*>(prm.x + i * 128 + lane * 4);
            float s = 0.f;
#pragma unroll
            for (int i = 0; i < 5; i++) s += (bf_lo(u[i].x) + bf_hi(u[i].x)) + (bf_lo(u[i].y) + bf_hi(u[i].y));
#pragma unroll
            for (int o = 16; o > 0; o >>= 1) s += __shfl_xor_sync(0xffffffffu, s, o);
            const float mean = s * (1.f / D_MODEL);
            s = 0.f;
#pragma unroll
            for (int i = 0; i < 5; i++) {
                const float a = bf_lo(u[i].x) - mean, b = bf_hi(u[i].x) - mean, c = bf_lo(u[i].y) - mean, d = bf_hi(u[i].y) - mean;
                s += fmaf(a, a, b * b) + fmaf(c, c, d * d);
            }
#pragma unroll
            for (int o = 16; o > 0; o >>= 1) s += __shfl_xor_sync(0xffffffffu, s, o);
            const float mean_b = bf16r(mean);
            float den;
            asm("sqrt.approx.f32 %0, %1;" : "=f"(den) : "f"(bf16r(bf16r(s * (1.f / D_MODEL)) + 1e-5f)));
            const float inv = rcp(bf16r(den));
#pragma unroll
            for (int i = 0; i < 5; i++) {
                const uint32_t d0 = pack_bf16(bf_lo(u[i].x) - mean_b, bf_hi(u[i].x) - mean_b);
                const uint32_t d1 = pack_bf16(bf_lo(u[i].y) - mean_b, bf_hi(u[i].y) - mean_b);
                u[i] = make_uint2(pack_bf16(bf_lo(d0) * inv, bf_hi(d0) * inv), pack_bf16(bf_lo(d1) * inv, bf_hi(d1) * inv));
            }
            cluster_wait();
#pragma unroll 1
            for (int d = 0; d < CL; d++) {
                const uint32_t dst = mapa(sb + SM_XN + lane * 8, d), mb = mapa(bar + BAR_X, d);
#pragma unroll
                for (int i = 0; i < 5; i++) st_async2(dst + i * 256, __uint_as_float(u[i].x), __uint_as_float(u[i].y), mb);
            }
        }
        __syncwarp();
    }
    if (warp == N_CONS_WARPS + 1 && rank < V_WARPS) {
        ll_store(g_x + D_FF + pair_head(cl, 1) * D_HEAD + rank * 32 + lane, 0u);
    } else if (warp > N_CONS_WARPS && (!owner || warp == N_CONS_WARPS + 1)) {
        named_arrive(6, n_start);
        return;
    }
    named_sync(6, n_start);
    mbar_wait(bar + BAR_X, 0);
    const uint32_t epoch = lds32(sb + SM_EPOCH);
    const uint32_t tag = 1u + (epoch & 1u);

    if (warp == N_CONS_WARPS + 1) {
        const bool fin = owner && rank < 4;
        const int col = cl * 64 + rank * 16 + (lane & 1) * 8 + ((lane >> 1) & 7);
        uint16_t* const out = reinterpret_cast<uint16_t*>(prm.out) + col;
        mbar_wait(bar + BAR_ML, 0);
        uint32_t xv = 0;
        if (fin) xv = reinterpret_cast<const uint16_t*>(prm.x)[col];
        float wv;
        {
            const uint32_t ma = sb + SM_ML + (lane < n_heads * CL ? lane : 0) * 8;
            const float mi = lds_f(ma);
            float m = fmaxf(mi, __shfl_xor_sync(0xffffffffu, mi, 1));
            m = fmaxf(m, __shfl_xor_sync(0xffffffffu, m, 2));
            m = fmaxf(m, __shfl_xor_sync(0xffffffffu, m, 4));
            const float ei = ex2((mi - m) * LOG2E);
            float den = ei * lds_f(ma + 4);
            den += __shfl_xor_sync(0xffffffffu, den, 1);
            den += __shfl_xor_sync(0xffffffffu, den, 2);
            den += __shfl_xor_sync(0xffffffffu, den, 4);
            wv = ei * rcp(den);
        }
#pragma unroll 1
        for (int hh = 0; hh < n_heads; hh++) {
            float w[CL];
#pragma unroll
            for (int s = 0; s < CL; s++) w[s] = __shfl_sync(0xffffffffu, wv, hh * CL + s);
            uint32_t* dst = g_x + D_FF + head_at(cl, hh, tri) * D_HEAD + rank * 32 + lane;
            const uint32_t src = sb + SM_OP + hh * 1024 + lane * 4;
            mbar_wait(bar + BAR_O + hh * 8, 0);
            float v[CL];
#pragma unroll
            for (int s = 0; s < CL; s++) v[s] = lds_f(src + s * 128);
            const float o = (fmaf(w[1], v[1], w[0] * v[0]) + fmaf(w[3], v[3], w[2] * v[2])) +
                            (fmaf(w[5], v[5], w[4] * v[4]) + fmaf(w[7], v[7], w[6] * v[6]));
            ll_store(dst, __float_as_uint(bf16r(o)) | tag);
        }
        if (fin) {
            mbar_wait(bar + BAR_G, 0);
            const uint32_t g = pack_bf16(silu_f(bf16r(lds_colsum(sb + SM_FG + lane * 4))), 0.f);
            asm volatile("{\n.reg .pred p;\nsetp.eq.u32 p, %2, 0;\n@p st.relaxed.gpu.global.b32 [%0], %1;\n}" ::"l"(g_epoch), "r"(epoch + 1u), "r"(cta + lane) : "memory");
            mbar_wait(bar + BAR_S, 0);
            uint32_t res = pack_bf16(lds_colsum(sb + SM_FS + lane * 4), 0.f);
            asm("mul.rn.bf16x2 %0, %0, %1;" : "+r"(res) : "r"(g));
            asm("add.rn.bf16x2 %0, %0, %1;" : "+r"(res) : "r"(xv));
            if (lane < 16) *out = (uint16_t)res;
        }
        return;
    }
    if (warp >= N_CONS_WARPS + 2) {
        const int gw = warp - (N_CONS_WARPS + 2);
        mbar_wait(bar + BAR_GO, 0);
#pragma unroll 1
        for (int round = 0; round < 2; round++) {
            const int i0 = round * 4 + 2 + gw;
            const uint32_t* src0 = g_x + tail_row(rank, i0) + lane * 4;
            const uint32_t* src1 = g_x + tail_row(rank, gw) + lane * 4;
            if (round == 1) {
                named_arrive(8, N_CONS + N_GATHER);
                mbar_wait(bar + BAR_GO + 8, 0);
                mbar_wait(bar_full + ((pos_t + GATE_LATE) & (N_SLOT - 1)) * 8, ((pos_t + GATE_LATE) >> 4) & 1);
            }
            uint4 v0 = make_uint4(0u, 0u, 0u, 0u), v1 = v0;
            const bool second = round == 0 && gw < 2 && lane < 24;
            uint32_t miss0 = lane < 24, miss1 = second;
            unsigned n = 0;
#pragma unroll 1
            while (true) {
                ll_ld4_if(v0, src0, miss0);
                ll_ld4_if(v1, src1, miss1);
                if (ll_bad4(v0, tag) == 0) miss0 = 0;
                if (ll_bad4(v1, tag) == 0) miss1 = 0;
                if (__all_sync(0xffffffffu, (miss0 | miss1) == 0) || ++n > SPIN_LIMIT) break;
            }
            if (lane < 24)
                *reinterpret_cast<uint2*>(sp + SM_OV + i0 * 192 + lane * 8) = make_uint2(__byte_perm(v0.x, v0.y, 0x7632), __byte_perm(v0.z, v0.w, 0x7632));
            if (second)
                *reinterpret_cast<uint2*>(sp + SM_OV + gw * 192 + lane * 8) = make_uint2(__byte_perm(v1.x, v1.y, 0x7632), __byte_perm(v1.z, v1.w, 0x7632));
        }
        named_arrive(3, N_CONS + N_GATHER);
        return;
    }


    const int q4 = lane & 3, g8 = lane >> 2;
    const int rowT = (lane & 7) + ((lane >> 4) << 3), hiT = (lane >> 3) & 1;
    const uint32_t off_v = ((3 * rowT + (warp >> 1)) * 128 + ((hiT ^ ((3 * rowT + (warp >> 1)) & 7)) << 4)) ^ ((warp & 1) << 6);

    if (warp < V_WARPS) {
#pragma unroll 1
        for (int part = 0; part <= tri; part++) {
            const uint32_t xa = sb + SM_XN + ((part ? rank * 16 - 1280 : (rank & 3) * 16) + 2 * q4) * 2, xs = 128 << part;
            float acc[2][4] = {};
#pragma unroll 1
            for (int p = part * 10; p < 10 + part * 5; p++) {
                const uint32_t b0 = lds32(xa + p * xs), b1 = lds32(xa + p * xs + 16);
                mbar_wait(bar_full + (POS_WQ + (p >> 1)) * 8, 0);
                uint32_t a[4];
                ldsm_x4_t(a, sb + SM_RING + POS_WQ * TILE_BYTES + p * PIECE_BYTES + off_v);
                mma_bf16(acc[0], a, b0, b1);
                ldsm_x4_t(a, sb + SM_RING + POS_WQ * TILE_BYTES + p * PIECE_BYTES + (off_v ^ 32));
                mma_bf16(acc[1], a, b0, b1);
                __syncwarp();
                if (lane == 0) mbar_arrive_n(bar_empty + (POS_WQ + (p >> 1)) * 8, p == 14 ? RELEASE / V_WARPS : RELEASE / V_WARPS / 2);
            }
            const float v = pick4(acc[0][0], acc[0][2], acc[1][0], acc[1][2], q4);
            const uint32_t dst = sb + SM_QP + ((part * CL + rank) * D_HEAD + warp * 32 + q4 * 8 + g8) * 4;
#pragma unroll
            for (int d = 0; d < CL; d++) st_async(mapa(dst, d), v, mapa(bar + BAR_Q, d));
        }
        mbar_wait(bar + BAR_Q, 0);
        const float* qp = reinterpret_cast<const float*>(sp + SM_QP) + tid;
        __nv_bfloat16* qs = reinterpret_cast<__nv_bfloat16*>(sp + SM_Q) + tid;
        qs[0] = __float2bfloat16_rn((qp[0] + qp[192]) + (qp[384] + qp[576]));
        qs[(tri + 1) * D_HEAD] = __float2bfloat16_rn((qp[768] + qp[960]) + (qp[1152] + qp[1344]));
        if (tri) {
            qp += CL * D_HEAD;
            qs[D_HEAD] = __float2bfloat16_rn(((qp[0] + qp[192]) + (qp[384] + qp[576])) + ((qp[768] + qp[960]) + (qp[1152] + qp[1344])));
        }
    } else {
        mbar_wait(bar_full + (warp - V_WARPS) * 8, 0);
    }
    named_sync(1, N_CONS);

    {
        const int rowN = (lane & 7) + (((lane >> 3) & 1) << 3), hiN = lane >> 4;
#pragma unroll 1
        for (int hh = 0; hh < n_heads; hh++) {
            float s0 = 0.f, s1 = 0.f;
#pragma unroll 1
            for (int i = 0; i < 2; i++) {
                const int u = hh * HEAD_TILES + i * 8 + warp, pos = u < 2 ? u : pos_k + u, slot = pos & (N_SLOT - 1);
                mbar_wait(bar_full + slot * 8, (pos >> 4) & 1);
                const uint32_t tb = sb + SM_RING + slot * TILE_BYTES;
                float acc[2][2][4] = {};
#pragma unroll 1
                for (int j = 0; j < 3; j++) {
                    const int swz = u < 2 ? 0 : (3 * rowN + j) & 7;
                    const uint32_t oj = tb + (3 * rowN + j) * 128 + ((hiN ^ swz) << 4);
                    const uint32_t qa = sb + SM_Q + (hh * D_HEAD + j * 64 + 2 * q4) * 2;
#pragma unroll
                    for (int k = 0; k < 4; k++) {
                        const uint32_t b0 = lds32(qa + k * 32), b1 = lds32(qa + k * 32 + 16);
                        uint32_t a[4];
                        ldsm_x4(a, oj ^ (k << 5));
                        mma_bf16(acc[0][k & 1], a, b0, b1);
                        ldsm_x4(a, (oj + PIECE_BYTES) ^ (k << 5));
                        mma_bf16(acc[1][k & 1], a, b0, b1);
                    }
                }
                __syncwarp();
                if (lane == 0) mbar_arrive_n(bar_empty + slot * 8, RELEASE);
                const float raw = pick4(acc[0][0][0] + acc[0][1][0], acc[0][0][2] + acc[0][1][2],
                                        acc[1][0][0] + acc[1][1][0], acc[1][0][2] + acc[1][1][2], q4);
                s0 = s1;
                s1 = bf16r(bf16r(raw) * 0.07216878364870323f);
            }
            float m = fmaxf(s0, s1);
#pragma unroll
            for (int o = 16; o > 0; o >>= 1) m = fmaxf(m, __shfl_xor_sync(0xffffffffu, m, o));
            if (lane == 0) sst[hh * 8 + warp] = m;
            named_sync(1, N_CONS);
#pragma unroll
            for (int w = 0; w < 8; w++) m = fmaxf(m, sst[hh * 8 + w]);
            const float p0 = ex2((s0 - m) * LOG2E), p1 = ex2((s1 - m) * LOG2E);
            float l = p0 + p1;
#pragma unroll
            for (int o = 16; o > 0; o >>= 1) l += __shfl_xor_sync(0xffffffffu, l, o);
            if (lane == 0) sst[24 + hh * 8 + warp] = l;
            __nv_bfloat16* ps = reinterpret_cast<__nv_bfloat16*>(sp + SM_P) + hh * 512 + warp * 32 + q4 * 8 + g8;
            ps[0] = __float2bfloat16_rn(p0);
            ps[256] = __float2bfloat16_rn(p1);
        }
        named_sync(1, N_CONS);
        if (warp == 7 && lane < n_heads * CL && (lane & 7) < V_WARPS) {
            const float* st = sst + (lane & 24);
            float m = st[0], l = st[24];
#pragma unroll
            for (int w = 1; w < 8; w++) { m = fmaxf(m, st[w]); l += st[24 + w]; }
            st_async2(mapa(sb + SM_ML + ((lane & 24) + rank) * 8, lane & 7), m, l, mapa(bar + BAR_ML, lane & 7));
        }
    }

    const uint32_t off_w = (warp >> 2) * PIECE_BYTES + rowT * 128 + (((((warp & 3) << 1) | hiT) ^ (rowT & 7)) << 4);

    if (ffn) {
#pragma unroll 1
        for (int res = 0; res < 2; res++) {
            float acc[3][4] = {};
#pragma unroll 1
            for (int i = 0; i < W_TILES / 2; i++) {
                const int pos = pos_w + res * (W_TILES / 2) + i, slot = pos & (N_SLOT - 1);
                const uint32_t xa = sb + SM_XN + (i * 96 + (warp >> 2) * 48 + 2 * q4) * 2;
                mbar_wait(bar_full + slot * 8, (pos >> 4) & 1);
#pragma unroll
                for (int k = 0; k < 3; k++) {
                    uint32_t a[4];
                    ldsm_x4_t(a, sb + SM_RING + slot * TILE_BYTES + off_w + k * 2048);
                    mma_bf16(acc[k], a, lds32(xa + k * 32), lds32(xa + k * 32 + 16));
                }
                __syncwarp();
                if (lane == 0) mbar_arrive_n(bar_empty + slot * 8, RELEASE / N_CONS_WARPS);
            }
            if (q4 < 2)
                reinterpret_cast<float*>(sp + SM_FG)[res * 128 + warp * 16 + q4 * 8 + g8] =
                    q4 ? (acc[0][2] + acc[1][2]) + acc[2][2] : (acc[0][0] + acc[1][0]) + acc[2][0];
        }
        named_sync(1, N_CONS);
        if (warp >= V_WARPS) {
            const float* f = reinterpret_cast<const float*>(sp + SM_FG) + (tid & 63);
            const float h = bf16r(bf16r(silu_f(bf16r(f[0] + f[64]))) * bf16r(f[128] + f[192]));
            ll_store(g_x + (cta - N_OWN * CL) * 64 + (tid & 63), __float_as_uint(h) | tag);
        }
    }

    if (warp < V_WARPS) {
        const uint32_t rdst = mapa(sb + SM_OP + rank * 128 + (q4 * 8 + g8) * 4, warp), rbar = mapa(bar + BAR_O, warp);
#pragma unroll 1
        for (int hh = 0; hh < n_heads; hh++) {
            float oacc[2][2][4] = {};
#pragma unroll 2
            for (int u = hh * HEAD_TILES; u < (hh + 1) * HEAD_TILES; u++) {
                const int pos = pos_v + u, slot = pos & (N_SLOT - 1);
                uint32_t ta = sb + SM_RING + slot * TILE_BYTES + off_v, tc = ta ^ 32;
                asm volatile("" : "+r"(ta), "+r"(tc));
                const uint32_t pa = sb + SM_P + (u * 32 + 2 * q4) * 2;
                const uint32_t b0 = lds32(pa), b1 = lds32(pa + 16), b2 = lds32(pa + 32), b3 = lds32(pa + 48);
                mbar_wait(bar_full + slot * 8, (pos >> 4) & 1);
                uint32_t a[4][4];
                ldsm_x4_t(a[0], ta);
                ldsm_x4_t(a[1], tc);
                ldsm_x4_t(a[2], ta + PIECE_BYTES);
                ldsm_x4_t(a[3], tc + PIECE_BYTES);
                mma_bf16(oacc[0][0], a[0], b0, b1);
                mma_bf16(oacc[1][0], a[1], b0, b1);
                mma_bf16(oacc[0][1], a[2], b2, b3);
                mma_bf16(oacc[1][1], a[3], b2, b3);
                __syncwarp();
                if (lane == 0) mbar_arrive_n(bar_empty + slot * 8, RELEASE / V_WARPS);
            }
            const float v = pick4(oacc[0][0][0] + oacc[0][1][0], oacc[0][0][2] + oacc[0][1][2],
                                  oacc[1][0][0] + oacc[1][1][0], oacc[1][0][2] + oacc[1][1][2], q4);
            st_async(rdst + hh * 1024, v, rbar + hh * 8);
        }
    }
    if (!owner) return;

    {
        constexpr int P0 = POS_K2 + 4 * HEAD_TILES;
        const uint32_t rdst = mapa(sb + SM_FG + (rank * 2 + (warp >> 2)) * 64 + g8 * 8, warp & 3);
        const uint32_t rbar = mapa(bar + BAR_G, warp & 3);
        const uint32_t va = sb + SM_OV + ((warp >> 2) * 48 + 2 * q4) * 2, tw = sb + SM_RING + off_w;
        named_sync(8, N_CONS + N_GATHER);
        auto send = [&](const float (&acc)[3][4], uint32_t dst, uint32_t mb) {
            if (q4 == 0) st_async2(dst, (acc[0][0] + acc[1][0]) + acc[2][0], (acc[0][2] + acc[1][2]) + acc[2][2], mb);
        };
        float acc[3][4] = {};
#pragma unroll 1
        for (int i = 0; i < 6; i++) {
            const int slot = (P0 + i) & (N_SLOT - 1);
            uint32_t b[3][2];
#pragma unroll
            for (int k = 0; k < 3; k++) { b[k][0] = lds32(va + i * 192 + k * 32); b[k][1] = lds32(va + i * 192 + k * 32 + 16); }
            mbar_wait(bar_full + slot * 8, ((P0 + i) >> 4) & 1);
#pragma unroll
            for (int k = 0; k < 3; k++) {
                uint32_t a[4];
                ldsm_x4_t(a, tw + slot * TILE_BYTES + k * 2048);
                mma_bf16(acc[k], a, b[k][0], b[k][1]);
            }
            if (i == 1) {
                send(acc, rdst, rbar);
#pragma unroll
                for (int k = 0; k < 3; k++) acc[k][0] = acc[k][1] = acc[k][2] = acc[k][3] = 0.f;
            }
        }
        uint32_t ae[LATE_EARLY + 1][3][4];
#pragma unroll
        for (int i = 0; i < LATE_EARLY; i++) {
            const int slot = (P0 + 6 + i) & (N_SLOT - 1);
            mbar_wait(bar_full + slot * 8, ((P0 + 6 + i) >> 4) & 1);
#pragma unroll
            for (int k = 0; k < 3; k++) ldsm_x4_t(ae[i][k], tw + slot * TILE_BYTES + k * 2048);
        }
        uint32_t da = rdst + (SM_FS - SM_FG), ba = rbar + (BAR_S - BAR_G);
        asm volatile("" : "+r"(da), "+r"(ba));
        named_sync(3, N_CONS + N_GATHER);
        uint32_t b[4][3][2];
#pragma unroll
        for (int i = 0; i < 4; i++)
#pragma unroll
            for (int k = 0; k < 3; k++) { b[i][k][0] = lds32(va + (6 + i) * 192 + k * 32); b[i][k][1] = lds32(va + (6 + i) * 192 + k * 32 + 16); }
#pragma unroll
        for (int i = 0; i < LATE_EARLY; i++)
#pragma unroll
            for (int k = 0; k < 3; k++) mma_bf16(acc[k], ae[i][k], b[i][k][0], b[i][k][1]);
#pragma unroll
        for (int i = LATE_EARLY; i < 4; i++) {
            const int slot = (P0 + 6 + i) & (N_SLOT - 1);
            mbar_wait(bar_full + slot * 8, ((P0 + 6 + i) >> 4) & 1);
            uint32_t a[3][4];
#pragma unroll
            for (int k = 0; k < 3; k++) ldsm_x4_t(a[k], tw + slot * TILE_BYTES + k * 2048);
#pragma unroll
            for (int k = 0; k < 3; k++) mma_bf16(acc[k], a[k], b[i][k][0], b[i][k][1]);
        }
        send(acc, da, ba);
    }
}

typedef CUresult (*EncodeTiledFn)(CUtensorMap*, CUtensorMapDataType, cuuint32_t, void*, const cuuint64_t*,
                                  const cuuint64_t*, const cuuint32_t*, const cuuint32_t*, CUtensorMapInterleave,
                                  CUtensorMapSwizzle, CUtensorMapL2promotion, CUtensorMapFloatOOBfill);

void encode_map(EncodeTiledFn fn, CUtensorMap* m, const void* base, cuuint64_t rows, cuuint64_t cols, cuuint32_t b1, cuuint32_t b2) {
    const cuuint64_t dims[3] = {64, cols / 64, rows};
    const cuuint64_t strides[2] = {128, cols * 2};
    const cuuint32_t box[3] = {64, b1, b2};
    const cuuint32_t estr[3] = {1, 1, 1};
    fn(m, CU_TENSOR_MAP_DATA_TYPE_BFLOAT16, 3, const_cast<void*>(base), dims, strides, box, estr,
       CU_TENSOR_MAP_INTERLEAVE_NONE, CU_TENSOR_MAP_SWIZZLE_128B, CU_TENSOR_MAP_L2_PROMOTION_NONE,
       CU_TENSOR_MAP_FLOAT_OOB_FILL_NONE);
}

}

extern "C" void kernel_launch(void* const* d_in, const int* in_sizes, int n_in, void* d_out, int out_size) {
    (void)in_sizes; (void)n_in; (void)out_size;
    static EncodeTiledFn encode = nullptr;
    static double pace_scale = 1.0;
    static void* scratch = nullptr;
    if (!encode) {
        int dev = 0, mem_khz = 0, bus_bits = 0;
        cudaGetDevice(&dev);
        cudaDeviceGetAttribute(&mem_khz, cudaDevAttrMemoryClockRate, dev);
        cudaDeviceGetAttribute(&bus_bits, cudaDevAttrGlobalMemoryBusWidth, dev);
        const double peak_gbs = 2.0 * mem_khz * 1e-6 * bus_bits / 8.0;
        if (peak_gbs > 0.0) pace_scale = PACE_REF_GBS / peak_gbs;
        void* fn = nullptr;
        cudaDriverEntryPointQueryResult qr;
        cudaGetDriverEntryPoint("cuTensorMapEncodeTiled", &fn, cudaEnableDefault, &qr);
        encode = reinterpret_cast<EncodeTiledFn>(fn);
        cudaFuncSetAttribute(fused_decode_kernel, cudaFuncAttributeMaxDynamicSharedMemorySize, SM_ALLOC);
        cudaGetSymbolAddress(&scratch, g_scratch);
    }
    CUtensorMap tm_k, tm_v, tm_wq, tm_w1, tm_w3, tm_wo, tm_w2;
    encode_map(encode, &tm_k, d_in[1], (cuuint64_t)N_HEAD * SEQ, D_HEAD, 3, 0 ? 16 : 32);
    encode_map(encode, &tm_v, d_in[2], (cuuint64_t)N_HEAD * SEQ, D_HEAD, 3, 0 ? 16 : 32);
    encode_map(encode, &tm_wq, d_in[3], D_MODEL, N_HEAD * D_HEAD, 3, 16);
    encode_map(encode, &tm_w1, d_in[6], D_MODEL, D_FF, 1, 0 ? 48 : 96);
    encode_map(encode, &tm_w3, d_in[7], D_MODEL, D_FF, 1, 0 ? 48 : 96);
    encode_map(encode, &tm_wo, d_in[4], N_HEAD * D_HEAD, D_MODEL, 1, 0 ? 48 : 96);
    encode_map(encode, &tm_w2, d_in[8], D_FF, D_MODEL, 1, 0 ? 48 : 96);
    Params prm;
    prm.x = static_cast<const __nv_bfloat16*>(d_in[0]);
    prm.out = static_cast<__nv_bfloat16*>(d_out);
    prm.k = static_cast<const __nv_bfloat16*>(d_in[1]) + (size_t)(SEQ - WIN) * D_HEAD;
    prm.scratch = static_cast<uint32_t*>(scratch);
    auto step = [&](double pace, double bytes, int pieces) { return (uint16_t)(8.0 * pace * pace_scale * bytes / (128.0 * TILE_BYTES) / pieces); };
    const double b_wq = 2.0 * D_MODEL * N_HEAD * D_HEAD;
    const double b_mid = 4.0 * N_HEAD * WIN * D_HEAD - 2.0 * N_CTA * TILE_BYTES + 4.0 * D_MODEL * D_FF;
    const double b_tail = 2.0 * D_MODEL * (D_FF + N_HEAD * D_HEAD);
    prm.step_wq2 = step(PACE_HEAD, b_wq, 10);
    prm.step_wq3 = step(PACE_HEAD, b_wq, 15);
    prm.step_own = step(PACE_MID, b_mid, 4 * HEAD_TILES - 2);
    prm.step_ffn = step(PACE_MID, b_mid, 4 * HEAD_TILES - 2 + W_TILES);
    prm.step_tri = step(PACE_MID, b_mid, 6 * HEAD_TILES - 2);
    prm.step_tail = step(PACE_TAIL, b_tail, TAIL_TILES);
    prm.late = (uint16_t)(4096.0 * PACE_LATE / PACE_MID + 0.5);
    prm.pad = N_CONS;
    fused_decode_kernel<<<N_CTA, N_THREADS, SM_ALLOC, cudaStreamPerThread>>>(prm, tm_wq, tm_w1, tm_w3, tm_k, tm_v, tm_wo, tm_w2);
}
```

```cpp
#include <cuda_runtime.h>
#include <cuda_bf16.h>
#include <cuda.h>
#include <stdint.h>

namespace {

constexpr int D_MODEL = 640;
constexpr int N_HEAD = 32;
constexpr int D_HEAD = 192;
constexpr int SEQ = 32768;
constexpr int WIN = 4096;
constexpr int D_FF = 1536;

constexpr int CL = 8;
constexpr int N_CL = 15;
constexpr int N_CTA = CL * N_CL;
constexpr int CL_FFN = 1, CL_TRI = CL_FFN + 3, CL_OWN = CL_TRI + 2;
constexpr int TILE_BYTES = 12288;
constexpr int PIECE_BYTES = TILE_BYTES / 2;
constexpr int N_SLOT = 16;
constexpr int HEAD_TILES = WIN / CL / 32;
constexpr int W_TILES = 14;
constexpr int TAIL_TILES = 10;
constexpr int POS_WQ = 2, POS_K2 = 5, POS_K3 = 8;

constexpr int N_CONS_WARPS = 8;
constexpr int N_CONS = N_CONS_WARPS * 32;
constexpr int N_GATHER = 128;
constexpr int N_THREADS = N_CONS + 64 + N_GATHER;
constexpr int V_WARPS = 6;
constexpr int RELEASE = 24;

constexpr double PACE_HEAD = 490, PACE_MID = 479, PACE_LATE = 495, PACE_TAIL = 478, PACE_REF_GBS = 3352.32;
constexpr int START_DELAY = 200;
constexpr int GATE_EARLY = 4;
constexpr int LATE_EARLY = 2;
constexpr int GATE_LATE = 3;

constexpr unsigned SPIN_LIMIT = 1u << 22;

constexpr int SM_RING = 0;
constexpr int SM_BAR = N_SLOT * TILE_BYTES;
constexpr int BAR_FULL = 0, BAR_EMPTY = 128, BAR_GO = 256, BAR_Q = 272, BAR_ML = 280, BAR_O = 288, BAR_G = 312, BAR_S = 320, BAR_X = 328,
              BAR_READY = 336;
constexpr int SM_T0 = SM_BAR + 448, SM_EPOCH = SM_BAR + 452;
constexpr int SM_XN = SM_BAR + 512;
constexpr int SM_Q = SM_XN + 1408;
constexpr int SM_ST = SM_Q + 1152;
constexpr int SM_ML = SM_ST + 256;
constexpr int SM_P = SM_ML + 256;
constexpr int SM_QP = SM_P + 3072;
constexpr int SM_OP = SM_QP + 12288;
constexpr int SM_OV = SM_OP + 3072;
constexpr int SM_FG = SM_OV + 1920;
constexpr int SM_FS = SM_FG + 1024;
constexpr int SM_ALLOC = SM_FS + 1024 + 1024;

constexpr int XO_H = 32;
constexpr int XO_END = XO_H + D_FF + N_HEAD * D_HEAD;
__device__ __align__(128) uint32_t g_scratch[XO_END];

__device__ __forceinline__ uint32_t smem_u32(const void* p) { return (uint32_t)__cvta_generic_to_shared(p); }

__device__ __forceinline__ void mbar_init(uint32_t bar, uint32_t cnt) {
    asm volatile("mbarrier.init.shared::cta.b64 [%0], %1;" ::"r"(bar), "r"(cnt) : "memory");
}
__device__ __forceinline__ void mbar_expect_tx(uint32_t bar, uint32_t bytes) {
    asm volatile("mbarrier.arrive.expect_tx.shared::cta.b64 _, [%0], %1;" ::"r"(bar), "r"(bytes) : "memory");
}
__device__ __forceinline__ void mbar_arrive(uint32_t bar) {
    asm volatile("mbarrier.arrive.shared::cta.b64 _, [%0];" ::"r"(bar) : "memory");
}
__device__ __forceinline__ void mbar_wait(uint32_t bar, uint32_t parity) {
    asm volatile(
        "{\n.reg .pred p, q;\n.reg .u32 n;\n"
        "mov.u32 n, 0;\n"
        "WAIT_LOOP:\n"
        "add.u32 n, n, 1;\n"
        "setp.lt.u32 q, n, %2;\n"
        "mbarrier.try_wait.parity.shared::cta.b64 p, [%0], %1;\n"
        "and.pred q, q, !p;\n"
        "@q bra WAIT_LOOP;\n}"
        ::"r"(bar), "r"(parity), "n"(SPIN_LIMIT) : "memory");
}
__device__ __forceinline__ void named_sync(int id, int n) {
    asm volatile("bar.sync %0, %1;" ::"r"(id), "r"(n) : "memory");
}
__device__ __forceinline__ void named_arrive(int id, int n) {
    asm volatile("bar.arrive %0, %1;" ::"r"(id), "r"(n) : "memory");
}
__device__ __forceinline__ uint64_t stream_policy() {
    uint64_t pol;
    asm volatile("createpolicy.fractional.L2::evict_first.b64 %0, 1.0;" : "=l"(pol));
    return pol;
}
__device__ __forceinline__ void bulk_load(uint32_t dst, const void* src, uint32_t bytes, uint32_t bar, uint64_t pol) {
    asm volatile("cp.async.bulk.shared::cluster.global.mbarrier::complete_tx::bytes.L2::cache_hint [%0], [%1], %2, [%3], %4;"
                 ::"r"(dst), "l"(src), "r"(bytes), "r"(bar), "l"(pol) : "memory");
}
__device__ __forceinline__ void tma_3d(uint32_t dst, const CUtensorMap* tm, int c0, int c1, int c2, uint32_t bar, uint64_t pol) {
    asm volatile("cp.async.bulk.tensor.3d.shared::cluster.global.mbarrier::complete_tx::bytes.L2::cache_hint [%0], [%1, {%3, %4, %5}], [%2], %6;"
                 ::"r"(dst), "l"(tm), "r"(bar), "r"(c0), "r"(c1), "r"(c2), "l"(pol) : "memory");
}
__device__ __forceinline__ void prefetch_tmap(const CUtensorMap* tm) {
    asm volatile("prefetch.tensormap [%0];" ::"l"(tm) : "memory");
}
__device__ __forceinline__ void ldsm_x4(uint32_t (&r)[4], uint32_t addr) {
    asm volatile("ldmatrix.sync.aligned.m8n8.x4.shared.b16 {%0,%1,%2,%3}, [%4];"
                 : "=r"(r[0]), "=r"(r[1]), "=r"(r[2]), "=r"(r[3]) : "r"(addr) : "memory");
}
__device__ __forceinline__ void ldsm_x4_t(uint32_t (&r)[4], uint32_t addr) {
    asm volatile("ldmatrix.sync.aligned.m8n8.x4.trans.shared.b16 {%0,%1,%2,%3}, [%4];"
                 : "=r"(r[0]), "=r"(r[1]), "=r"(r[2]), "=r"(r[3]) : "r"(addr) : "memory");
}
__device__ __forceinline__ void mma_bf16(float (&c)[4], const uint32_t (&a)[4], uint32_t b0, uint32_t b1) {
    asm volatile("mma.sync.aligned.m16n8k16.row.col.f32.bf16.bf16.f32 {%0,%1,%2,%3}, {%4,%5,%6,%7}, {%8,%9}, {%0,%1,%2,%3};"
                 : "+f"(c[0]), "+f"(c[1]), "+f"(c[2]), "+f"(c[3])
                 : "r"(a[0]), "r"(a[1]), "r"(a[2]), "r"(a[3]), "r"(b0), "r"(b1));
}
__device__ __forceinline__ float bf16r(float v) {
    uint32_t p;
    asm("cvt.rn.bf16x2.f32 %0, %1, %2;" : "=r"(p) : "f"(v), "f"(0.f));
    return __uint_as_float(p);
}
__device__ __forceinline__ uint32_t lds32(uint32_t addr) {
    uint32_t v;
    asm volatile("ld.shared.b32 %0, [%1];" : "=r"(v) : "r"(addr) : "memory");
    return v;
}
__device__ __forceinline__ float bf_lo(uint32_t v) { return __uint_as_float(v << 16); }
__device__ __forceinline__ float bf_hi(uint32_t v) { return __uint_as_float(v & 0xffff0000u); }
__device__ __forceinline__ uint32_t pack_bf16(float lo, float hi) {
    const __nv_bfloat162 p = __floats2bfloat162_rn(lo, hi);
    return *reinterpret_cast<const uint32_t*>(&p);
}
__device__ __forceinline__ uint32_t now_ns() {
    unsigned long long t;
    asm volatile("mov.u64 %0, %%globaltimer;" : "=l"(t));
    return (uint32_t)t;
}

__device__ __forceinline__ void wait_until(uint32_t t_start, uint32_t deadline) {
    unsigned n = 0;
    while (now_ns() - t_start < deadline && ++n < SPIN_LIMIT) {}
}

__device__ __forceinline__ uint32_t ll_bad4(const uint4& v, uint32_t tag) {
    uint32_t lo, hi;
    asm("lop3.b32 %0, %1, %2, %3, 0x7E;" : "=r"(lo) : "r"(v.x), "r"(v.y), "r"(tag));
    asm("lop3.b32 %0, %1, %2, %3, 0x7E;" : "=r"(hi) : "r"(v.z), "r"(v.w), "r"(tag));
    return (lo | hi) & 3u;
}
__device__ __forceinline__ float ex2(float v) {
    float r;
    asm("ex2.approx.ftz.f32 %0, %1;" : "=f"(r) : "f"(v));
    return r;
}
__device__ __forceinline__ float rcp(float v) {
    float r;
    asm("rcp.approx.ftz.f32 %0, %1;" : "=f"(r) : "f"(v));
    return r;
}
constexpr float LOG2E = 1.4426950408889634f;
__device__ __forceinline__ void ll_store(uint32_t* p, uint32_t w) {
    asm volatile("st.relaxed.gpu.global.b32 [%0], %1;" ::"l"(p), "r"(w) : "memory");
}
__device__ __forceinline__ uint32_t ll_ld(const uint32_t* p) {
    uint32_t v;
    asm volatile("ld.relaxed.gpu.global.b32 %0, [%1];" : "=r"(v) : "l"(p) : "memory");
    return v;
}
__device__ __forceinline__ float pick4(float a, float b, float c, float d, int j) {
    const float lo = (j & 1) ? b : a, hi = (j & 1) ? d : c;
    return (j & 2) ? hi : lo;
}
__device__ __forceinline__ float silu_f(float v) { return v * rcp(1.f + ex2(-LOG2E * v)); }

__device__ __forceinline__ void mbar_arrive_n(uint32_t bar, uint32_t n) {
    asm volatile("mbarrier.arrive.shared::cta.b64 _, [%0], %1;" ::"r"(bar), "r"(n) : "memory");
}
__device__ __forceinline__ uint32_t mapa(uint32_t addr, uint32_t rank) {
    uint32_t d;
    asm("mapa.shared::cluster.u32 %0, %1, %2;" : "=r"(d) : "r"(addr), "r"(rank));
    return d;
}
__device__ __forceinline__ void st_async(uint32_t dst, float v, uint32_t bar) {
    asm volatile("st.async.weak.shared::cluster.mbarrier::complete_tx::bytes.f32 [%0], %1, [%2];" ::"r"(dst), "f"(v), "r"(bar) : "memory");
}
__device__ __forceinline__ void st_async2(uint32_t dst, float a, float b, uint32_t bar) {
    asm volatile("st.async.weak.shared::cluster.mbarrier::complete_tx::bytes.v2.f32 [%0], {%1, %2}, [%3];" ::"r"(dst), "f"(a), "f"(b), "r"(bar) : "memory");
}
__device__ __forceinline__ void cluster_arrive() { asm volatile("barrier.cluster.arrive.relaxed.aligned;" ::: "memory"); }
__device__ __forceinline__ void cluster_wait() { asm volatile("barrier.cluster.wait.aligned;" ::: "memory"); }
__device__ __forceinline__ void ll_ld4_if(uint4& v, const uint32_t* p, uint32_t cond) {
    asm volatile("{\n.reg .pred p;\nsetp.ne.u32 p, %5, 0;\n@p ld.relaxed.gpu.global.v4.b32 {%0,%1,%2,%3}, [%4];\n}"
                 : "+r"(v.x), "+r"(v.y), "+r"(v.z), "+r"(v.w) : "l"(p), "r"(cond) : "memory");
}
__device__ __forceinline__ float lds_f(uint32_t addr) { return __uint_as_float(lds32(addr)); }
__device__ __forceinline__ float lds_colsum(uint32_t addr) {
    float v[8];
#pragma unroll
    for (int i = 0; i < 8; i++) v[i] = lds_f(addr + i * 128);
    const float s = ((v[0] + v[1]) + (v[2] + v[3])) + ((v[4] + v[5]) + (v[6] + v[7]));
    return s + __shfl_xor_sync(0xffffffffu, s, 16);
}

constexpr uint32_t FIRST_MUL = 257, FIRST_MASK = 0x7807;
__device__ __forceinline__ int pair_head(int cl, int j) { return 2 * cl + j; }
__device__ __forceinline__ int third_head(int cl) { return 2 * N_CL + cl - CL_TRI; }
__device__ __forceinline__ int head_at(int cl, int hh, int tri) { return (hh & tri) ? third_head(cl) : pair_head(cl, hh >> tri); }
__device__ __forceinline__ int tail_row(int rank, int i) {
    if (i < 2) return i * 768 + rank * 96;
    const int j = 4 * (i - 2) + (rank >> 1), q = rank & 1;
    return D_FF + (2 * (j & 15) + (j >> 4)) * D_HEAD + q * 96;
}

struct Params {
    const __nv_bfloat16* x;
    __nv_bfloat16* out;
    const __nv_bfloat16* k;
    uint32_t* scratch;
    uint16_t step_wq2, step_wq3, step_own, step_ffn, step_tri, step_tail, late, pad;
};
static_assert(sizeof(Params) == 48, "Params must fill the rest of the first parameter line");

__global__ void __cluster_dims__(CL, 1, 1) __launch_bounds__(N_THREADS, 1)
fused_decode_kernel(const Params prm, const __grid_constant__ CUtensorMap tm_wq, const __grid_constant__ CUtensorMap tm_w1,
                    const __grid_constant__ CUtensorMap tm_w3, const __grid_constant__ CUtensorMap tm_k,
                    const __grid_constant__ CUtensorMap tm_v, const __grid_constant__ CUtensorMap tm_wo,
                    const __grid_constant__ CUtensorMap tm_w2) {
    extern __shared__ uint8_t smem_raw[];
    asm volatile("{\n.reg .pred p;\nsetp.lt.u32 p, %1, %2;\n@p prefetch.global.L2 [%0];\n}"
                 ::"l"(reinterpret_cast<const char*>(prm.k) + (size_t)(((blockIdx.x * FIRST_MUL) & FIRST_MASK) * (TILE_BYTES / 32) + threadIdx.x) * 32),
                   "r"(threadIdx.x), "n"(TILE_BYTES / 32) : "memory");
    const uint32_t sb = (smem_u32(smem_raw) + 1023u) & ~1023u;
    uint8_t* sp = smem_raw + (sb - smem_u32(smem_raw));
    const uint32_t bar = sb + SM_BAR;
    const uint32_t bar_full = bar + BAR_FULL, bar_empty = bar + BAR_EMPTY;

    const int tid = threadIdx.x;
    const int cta = blockIdx.x, cl = blockIdx.x / CL, rank = blockIdx.x % CL;
    const int tri = cl >= CL_TRI && cl < CL_OWN;
    const int pos_k = tri ? POS_K3 : POS_K2;
    volatile uint32_t* t_first = reinterpret_cast<volatile uint32_t*>(sp + SM_T0);
    if (tid == N_CONS) {
        const __nv_bfloat16* k0 = prm.k + (uint32_t)(pair_head(cl, 0) * SEQ + rank * 32) * (size_t)D_HEAD;
#pragma unroll
        for (int u = 0; u < 2; u++) {
            mbar_init(bar_full + u * 8, 1);
            asm volatile("fence.mbarrier_init.release.cluster;" ::: "memory");
            mbar_expect_tx(bar_full + u * 8, TILE_BYTES);
            bulk_load(sb + SM_RING + u * TILE_BYTES, k0 + u * (CL * 32 * D_HEAD), TILE_BYTES, bar_full + u * 8, stream_policy());
            if (u == 0) *t_first = now_ns();
        }
    }
    if (tid == N_CONS + 32) prefetch_tmap(&tm_wq);
    const int warp = __shfl_sync(0xffffffffu, tid >> 5, 0), lane = tid & 31;
    const bool owner = cl < CL_FFN || cl >= CL_OWN, ffn = !owner && !tri;
    const int oc = cl < CL_FFN ? cl : cl - (CL_OWN - CL_FFN);
    const int n_heads = 2 + tri;
    const int pos_w = pos_k + n_heads * HEAD_TILES;
    const int pos_v = pos_w + (ffn ? W_TILES : 0);
    const int pos_t = pos_v + n_heads * HEAD_TILES;
    uint32_t* const g_epoch = prm.scratch;
    uint32_t* const g_x = prm.scratch + XO_H;
    const int n_start = owner ? N_THREADS : N_THREADS - 96;

    if (warp == N_CONS_WARPS) {
        if (lane == 0) {
#pragma unroll
            for (int i = 2; i < N_SLOT; i++) mbar_init(bar_full + i * 8, 1);
            mbar_init(bar + BAR_READY, 1);
            asm volatile("fence.mbarrier_init.release.cluster;" ::: "memory");
        }
        __syncwarp();
        named_arrive(6, n_start);
        cluster_arrive();
        if (lane == 0) {
            const uint64_t pol = stream_policy();
            const uint32_t t_start = *t_first;
            uint32_t deadline = START_DELAY * 8;
            {
                const uint32_t step = tri ? prm.step_wq3 : prm.step_wq2;
#pragma unroll 1
                for (int p = 0; p < 10 + 5 * tri; p++) {
                    const uint32_t fb = bar_full + (POS_WQ + (p >> 1)) * 8;
                    if (!(p & 1)) mbar_expect_tx(fb, p == 14 ? PIECE_BYTES : TILE_BYTES);
                    const int h = p < 10 ? pair_head(cl, rank >> 2) : third_head(cl);
                    const int row = p < 10 ? p * 64 + (rank & 3) * 16 : (p - 10) * 128 + rank * 16;
                    wait_until(t_start, deadline >> 3);
                    tma_3d(sb + SM_RING + POS_WQ * TILE_BYTES + p * PIECE_BYTES, &tm_wq, 0, h * 3, row, fb, pol);
                    deadline += step;
                }
            }
            mbar_wait(bar + BAR_READY, 0);
            uint32_t step = owner ? prm.step_own : (tri ? prm.step_tri : prm.step_ffn);
            const int pos_end = pos_t + (owner ? TAIL_TILES : 0);
            const int pos_late = pos_t - (owner ? 16 : (tri ? 24 : 20));
#pragma unroll 1
            for (int pos = pos_k + 2; pos < pos_end; pos++) {
                const int slot = pos & (N_SLOT - 1);
                const CUtensorMap* tm;
                int c1 = 0, row;
                if (pos >= pos_t) {
                    step = prm.step_tail;
                    row = tail_row(rank, pos - pos_t);
                    tm = row < D_FF ? &tm_w2 : &tm_wo;
                    if (row >= D_FF) row -= D_FF;
                    c1 = oc;
                } else if (pos >= pos_w && pos < pos_v) {
                    const bool up = pos >= pos_w + W_TILES / 2;
                    tm = up ? &tm_w3 : &tm_w1;
                    c1 = cta - CL_FFN * CL;
                    row = (pos - pos_w - (up ? W_TILES / 2 : 0)) * 96;
                } else {
                    const int u = pos - (pos < pos_w ? pos_k : pos_v), hh = u >> 4;
                    tm = pos < pos_w ? &tm_k : &tm_v;
                    row = head_at(cl, hh, tri) * SEQ + (SEQ - WIN) + rank * 32 + (u & 15) * (CL * 32);
                }
                if (pos >= N_SLOT) mbar_wait(bar_empty + slot * 8, ((pos >> 4) - 1) & 1);
                mbar_expect_tx(bar_full + slot * 8, TILE_BYTES);
                wait_until(t_start, deadline >> 3);
                tma_3d(sb + SM_RING + slot * TILE_BYTES, tm, 0, c1, row, bar_full + slot * 8, pol);
                deadline += step;
                if (pos == pos_late) step = step * prm.late >> 12;
                if (pos == pos_t - GATE_EARLY) mbar_arrive(bar + BAR_GO);
                if (pos == pos_t + GATE_LATE) mbar_arrive(bar + BAR_GO + 8);
            }
        }
        return;
    }

    if (warp > N_CONS_WARPS + 2 && !owner) return;
    if (tid == N_CONS + 32) {
#pragma unroll
        for (int i = 0; i < N_SLOT; i++) mbar_init(bar_empty + i * 8, RELEASE);
        asm volatile("fence.mbarrier_init.release.cluster;" ::: "memory");
    }
    if (tid == N_CONS + 64) {
#pragma unroll
        for (int i = BAR_GO; i <= BAR_X; i += 8) mbar_init(bar + i, 1);
        mbar_expect_tx(bar + BAR_X, D_MODEL * 2 + 4);
        mbar_expect_tx(bar + BAR_Q, (1 + tri) * CL * D_HEAD * 4);
        mbar_expect_tx(bar + BAR_ML, n_heads * CL * 8);
#pragma unroll
        for (int i = BAR_O; i <= BAR_S; i += 8) mbar_expect_tx(bar + i, 1024);
        asm volatile("fence.mbarrier_init.release.cluster;" ::: "memory");
    }
    __syncwarp();
    cluster_arrive();
    float* sst = reinterpret_cast<float*>(sp + SM_ST);
    if (tid < 8) *reinterpret_cast<uint2*>(sp + SM_XN + D_MODEL * 2 + tid * 8) = make_uint2(0u, 0u);
    if (rank == CL - 1 && warp >= V_WARPS && warp < N_CONS_WARPS) {
        if (warp == V_WARPS) {
            const uint32_t ep = ll_ld(g_epoch);
            cluster_wait();
            if (lane < CL) st_async(mapa(sb + SM_EPOCH, lane), __uint_as_float(ep), mapa(bar + BAR_X, lane));
        } else {
            uint2 u[5];
#pragma unroll
            for (int i = 0; i < 5; i++) u[i] = *reinterpret_cast<const uint2*>(prm.x + i * 128 + lane * 4);
            float s = 0.f;
#pragma unroll
            for (int i = 0; i < 5; i++) s += (bf_lo(u[i].x) + bf_hi(u[i].x)) + (bf_lo(u[i].y) + bf_hi(u[i].y));
#pragma unroll
            for (int o = 16; o > 0; o >>= 1) s += __shfl_xor_sync(0xffffffffu, s, o);
            const float mean = s * (1.f / D_MODEL);
            s = 0.f;
#pragma unroll
            for (int i = 0; i < 5; i++) {
                const float a = bf_lo(u[i].x) - mean, b = bf_hi(u[i].x) - mean, c = bf_lo(u[i].y) - mean, d = bf_hi(u[i].y) - mean;
                s += fmaf(a, a, b * b) + fmaf(c, c, d * d);
            }
#pragma unroll
            for (int o = 16; o > 0; o >>= 1) s += __shfl_xor_sync(0xffffffffu, s, o);
            const float mean_b = bf16r(mean);
            float den;
            asm("sqrt.approx.f32 %0, %1;" : "=f"(den) : "f"(bf16r(bf16r(s * (1.f / D_MODEL)) + 1e-5f)));
            const float inv = rcp(bf16r(den));
#pragma unroll
            for (int i = 0; i < 5; i++) {
                const uint32_t d0 = pack_bf16(bf_lo(u[i].x) - mean_b, bf_hi(u[i].x) - mean_b);
                const uint32_t d1 = pack_bf16(bf_lo(u[i].y) - mean_b, bf_hi(u[i].y) - mean_b);
                u[i] = make_uint2(pack_bf16(bf_lo(d0) * inv, bf_hi(d0) * inv), pack_bf16(bf_lo(d1) * inv, bf_hi(d1) * inv));
            }
            cluster_wait();
#pragma unroll 1
            for (int d = 0; d < CL; d++) {
                const uint32_t dst = mapa(sb + SM_XN + lane * 8, d), mb = mapa(bar + BAR_X, d);
#pragma unroll
                for (int i = 0; i < 5; i++) st_async2(dst + i * 256, __uint_as_float(u[i].x), __uint_as_float(u[i].y), mb);
            }
        }
        __syncwarp();
    }
    if (warp == N_CONS_WARPS + 1 && rank < V_WARPS) {
        ll_store(g_x + D_FF + pair_head(cl, 1) * D_HEAD + rank * 32 + lane, 0u);
    } else if (warp > N_CONS_WARPS && (!owner || warp == N_CONS_WARPS + 1)) {
        named_arrive(6, n_start);
        return;
    }
    named_sync(6, n_start);
    if (tid == 0) mbar_arrive(bar + BAR_READY);
    mbar_wait(bar + BAR_X, 0);
    const uint32_t epoch = lds32(sb + SM_EPOCH);
    const uint32_t tag = 1u + (epoch & 1u);

    if (warp == N_CONS_WARPS + 1) {
        const bool fin = owner && rank < 4;
        const int col = oc * 64 + rank * 16 + (lane & 1) * 8 + ((lane >> 1) & 7);
        uint16_t* const out = reinterpret_cast<uint16_t*>(prm.out) + col;
        mbar_wait(bar + BAR_ML, 0);
        uint32_t xv = 0;
        if (fin) xv = reinterpret_cast<const uint16_t*>(prm.x)[col];
        float wv;
        {
            const uint32_t ma = sb + SM_ML + (lane < n_heads * CL ? lane : 0) * 8;
            const float mi = lds_f(ma);
            float m = fmaxf(mi, __shfl_xor_sync(0xffffffffu, mi, 1));
            m = fmaxf(m, __shfl_xor_sync(0xffffffffu, m, 2));
            m = fmaxf(m, __shfl_xor_sync(0xffffffffu, m, 4));
            const float ei = ex2((mi - m) * LOG2E);
            float den = ei * lds_f(ma + 4);
            den += __shfl_xor_sync(0xffffffffu, den, 1);
            den += __shfl_xor_sync(0xffffffffu, den, 2);
            den += __shfl_xor_sync(0xffffffffu, den, 4);
            wv = ei * rcp(den);
        }
#pragma unroll 1
        for (int hh = 0; hh < n_heads; hh++) {
            float w[CL];
#pragma unroll
            for (int s = 0; s < CL; s++) w[s] = __shfl_sync(0xffffffffu, wv, hh * CL + s);
            uint32_t* dst = g_x + D_FF + head_at(cl, hh, tri) * D_HEAD + rank * 32 + lane;
            const uint32_t src = sb + SM_OP + hh * 1024 + lane * 4;
            mbar_wait(bar + BAR_O + hh * 8, 0);
            float v[CL];
#pragma unroll
            for (int s = 0; s < CL; s++) v[s] = lds_f(src + s * 128);
            const float o = (fmaf(w[1], v[1], w[0] * v[0]) + fmaf(w[3], v[3], w[2] * v[2])) +
                            (fmaf(w[5], v[5], w[4] * v[4]) + fmaf(w[7], v[7], w[6] * v[6]));
            ll_store(dst, __float_as_uint(bf16r(o)) | tag);
        }
        if (fin) {
            mbar_wait(bar + BAR_G, 0);
            const uint32_t g = pack_bf16(silu_f(bf16r(lds_colsum(sb + SM_FG + lane * 4))), 0.f);
            asm volatile("{\n.reg .pred p;\nsetp.eq.u32 p, %2, 0;\n@p st.relaxed.gpu.global.b32 [%0], %1;\n}" ::"l"(g_epoch), "r"(epoch + 1u), "r"(oc + rank + lane) : "memory");
            mbar_wait(bar + BAR_S, 0);
            uint32_t res = pack_bf16(lds_colsum(sb + SM_FS + lane * 4), 0.f);
            asm("mul.rn.bf16x2 %0, %0, %1;" : "+r"(res) : "r"(g));
            asm("add.rn.bf16x2 %0, %0, %1;" : "+r"(res) : "r"(xv));
            if (lane < 16) *out = (uint16_t)res;
        }
        return;
    }
    if (warp >= N_CONS_WARPS + 2) {
        const int gw = warp - (N_CONS_WARPS + 2);
        mbar_wait(bar + BAR_GO, 0);
#pragma unroll 1
        for (int round = 0; round < 2; round++) {
            const int i0 = round * 4 + 2 + gw;
            const uint32_t* src0 = g_x + tail_row(rank, i0) + lane * 4;
            const uint32_t* src1 = g_x + tail_row(rank, gw) + lane * 4;
            if (round == 1) {
                named_arrive(8, N_CONS + N_GATHER);
                mbar_wait(bar + BAR_GO + 8, 0);
                mbar_wait(bar_full + ((pos_t + GATE_LATE) & (N_SLOT - 1)) * 8, ((pos_t + GATE_LATE) >> 4) & 1);
            }
            uint4 v0 = make_uint4(0u, 0u, 0u, 0u), v1 = v0;
            const bool second = round == 0 && gw < 2 && lane < 24;
            uint32_t miss0 = lane < 24, miss1 = second;
            unsigned n = 0;
#pragma unroll 1
            while (true) {
                ll_ld4_if(v0, src0, miss0);
                ll_ld4_if(v1, src1, miss1);
                if (ll_bad4(v0, tag) == 0) miss0 = 0;
                if (ll_bad4(v1, tag) == 0) miss1 = 0;
                if (__all_sync(0xffffffffu, (miss0 | miss1) == 0) || ++n > SPIN_LIMIT) break;
            }
            if (lane < 24)
                *reinterpret_cast<uint2*>(sp + SM_OV + i0 * 192 + lane * 8) = make_uint2(__byte_perm(v0.x, v0.y, 0x7632), __byte_perm(v0.z, v0.w, 0x7632));
            if (second)
                *reinterpret_cast<uint2*>(sp + SM_OV + gw * 192 + lane * 8) = make_uint2(__byte_perm(v1.x, v1.y, 0x7632), __byte_perm(v1.z, v1.w, 0x7632));
        }
        named_arrive(3, N_CONS + N_GATHER);
        return;
    }


    const int q4 = lane & 3, g8 = lane >> 2;
    const int rowT = (lane & 7) + ((lane >> 4) << 3), hiT = (lane >> 3) & 1;
    const uint32_t off_v = ((3 * rowT + (warp >> 1)) * 128 + ((hiT ^ ((3 * rowT + (warp >> 1)) & 7)) << 4)) ^ ((warp & 1) << 6);

    if (warp < V_WARPS) {
#pragma unroll 1
        for (int part = 0; part <= tri; part++) {
            const uint32_t xa = sb + SM_XN + ((part ? rank * 16 - 1280 : (rank & 3) * 16) + 2 * q4) * 2, xs = 128 << part;
            float acc[2][4] = {};
#pragma unroll 1
            for (int p = part * 10; p < 10 + part * 5; p++) {
                const uint32_t b0 = lds32(xa + p * xs), b1 = lds32(xa + p * xs + 16);
                mbar_wait(bar_full + (POS_WQ + (p >> 1)) * 8, 0);
                uint32_t a[4];
                ldsm_x4_t(a, sb + SM_RING + POS_WQ * TILE_BYTES + p * PIECE_BYTES + off_v);
                mma_bf16(acc[0], a, b0, b1);
                ldsm_x4_t(a, sb + SM_RING + POS_WQ * TILE_BYTES + p * PIECE_BYTES + (off_v ^ 32));
                mma_bf16(acc[1], a, b0, b1);
                __syncwarp();
                if (lane == 0) mbar_arrive_n(bar_empty + (POS_WQ + (p >> 1)) * 8, p == 14 ? RELEASE / V_WARPS : RELEASE / V_WARPS / 2);
            }
            const float v = pick4(acc[0][0], acc[0][2], acc[1][0], acc[1][2], q4);
            const uint32_t dst = sb + SM_QP + ((part * CL + rank) * D_HEAD + warp * 32 + q4 * 8 + g8) * 4;
#pragma unroll
            for (int d = 0; d < CL; d++) st_async(mapa(dst, d), v, mapa(bar + BAR_Q, d));
        }
        mbar_wait(bar + BAR_Q, 0);
        const float* qp = reinterpret_cast<const float*>(sp + SM_QP) + tid;
        __nv_bfloat16* qs = reinterpret_cast<__nv_bfloat16*>(sp + SM_Q) + tid;
        qs[0] = __float2bfloat16_rn((qp[0] + qp[192]) + (qp[384] + qp[576]));
        qs[(tri + 1) * D_HEAD] = __float2bfloat16_rn((qp[768] + qp[960]) + (qp[1152] + qp[1344]));
        if (tri) {
            qp += CL * D_HEAD;
            qs[D_HEAD] = __float2bfloat16_rn(((qp[0] + qp[192]) + (qp[384] + qp[576])) + ((qp[768] + qp[960]) + (qp[1152] + qp[1344])));
        }
    } else {
        mbar_wait(bar_full + (warp - V_WARPS) * 8, 0);
    }
    named_sync(1, N_CONS);

    {
        const int rowN = (lane & 7) + (((lane >> 3) & 1) << 3), hiN = lane >> 4;
#pragma unroll 1
        for (int hh = 0; hh < n_heads; hh++) {
            float s0 = 0.f, s1 = 0.f;
#pragma unroll 1
            for (int i = 0; i < 2; i++) {
                const int u = hh * HEAD_TILES + i * 8 + warp, pos = u < 2 ? u : pos_k + u, slot = pos & (N_SLOT - 1);
                mbar_wait(bar_full + slot * 8, (pos >> 4) & 1);
                const uint32_t tb = sb + SM_RING + slot * TILE_BYTES;
                float acc[2][2][4] = {};
#pragma unroll 1
                for (int j = 0; j < 3; j++) {
                    const int swz = u < 2 ? 0 : (3 * rowN + j) & 7;
                    const uint32_t oj = tb + (3 * rowN + j) * 128 + ((hiN ^ swz) << 4);
                    const uint32_t qa = sb + SM_Q + (hh * D_HEAD + j * 64 + 2 * q4) * 2;
#pragma unroll
                    for (int k = 0; k < 4; k++) {
                        const uint32_t b0 = lds32(qa + k * 32), b1 = lds32(qa + k * 32 + 16);
                        uint32_t a[4];
                        ldsm_x4(a, oj ^ (k << 5));
                        mma_bf16(acc[0][k & 1], a, b0, b1);
                        ldsm_x4(a, (oj + PIECE_BYTES) ^ (k << 5));
                        mma_bf16(acc[1][k & 1], a, b0, b1);
                    }
                }
                __syncwarp();
                if (lane == 0) mbar_arrive_n(bar_empty + slot * 8, RELEASE);
                const float raw = pick4(acc[0][0][0] + acc[0][1][0], acc[0][0][2] + acc[0][1][2],
                                        acc[1][0][0] + acc[1][1][0], acc[1][0][2] + acc[1][1][2], q4);
                s0 = s1;
                s1 = bf16r(bf16r(raw) * 0.07216878364870323f);
            }
            float m = fmaxf(s0, s1);
#pragma unroll
            for (int o = 16; o > 0; o >>= 1) m = fmaxf(m, __shfl_xor_sync(0xffffffffu, m, o));
            if (lane == 0) sst[hh * 8 + warp] = m;
            named_sync(1, N_CONS);
#pragma unroll
            for (int w = 0; w < 8; w++) m = fmaxf(m, sst[hh * 8 + w]);
            const float p0 = ex2((s0 - m) * LOG2E), p1 = ex2((s1 - m) * LOG2E);
            float l = p0 + p1;
#pragma unroll
            for (int o = 16; o > 0; o >>= 1) l += __shfl_xor_sync(0xffffffffu, l, o);
            if (lane == 0) sst[24 + hh * 8 + warp] = l;
            __nv_bfloat16* ps = reinterpret_cast<__nv_bfloat16*>(sp + SM_P) + hh * 512 + warp * 32 + q4 * 8 + g8;
            ps[0] = __float2bfloat16_rn(p0);
            ps[256] = __float2bfloat16_rn(p1);
        }
        named_sync(1, N_CONS);
        if (warp == 7 && lane < n_heads * CL && (lane & 7) < V_WARPS) {
            const float* st = sst + (lane & 24);
            float m = st[0], l = st[24];
#pragma unroll
            for (int w = 1; w < 8; w++) { m = fmaxf(m, st[w]); l += st[24 + w]; }
            st_async2(mapa(sb + SM_ML + ((lane & 24) + rank) * 8, lane & 7), m, l, mapa(bar + BAR_ML, lane & 7));
        }
    }

    const uint32_t off_w = (warp >> 2) * PIECE_BYTES + rowT * 128 + (((((warp & 3) << 1) | hiT) ^ (rowT & 7)) << 4);

    if (ffn) {
#pragma unroll 1
        for (int res = 0; res < 2; res++) {
            float acc[3][4] = {};
#pragma unroll 1
            for (int i = 0; i < W_TILES / 2; i++) {
                const int pos = pos_w + res * (W_TILES / 2) + i, slot = pos & (N_SLOT - 1);
                const uint32_t xa = sb + SM_XN + (i * 96 + (warp >> 2) * 48 + 2 * q4) * 2;
                mbar_wait(bar_full + slot * 8, (pos >> 4) & 1);
#pragma unroll
                for (int k = 0; k < 3; k++) {
                    uint32_t a[4];
                    ldsm_x4_t(a, sb + SM_RING + slot * TILE_BYTES + off_w + k * 2048);
                    mma_bf16(acc[k], a, lds32(xa + k * 32), lds32(xa + k * 32 + 16));
                }
                __syncwarp();
                if (lane == 0) mbar_arrive_n(bar_empty + slot * 8, RELEASE / N_CONS_WARPS);
            }
            if (q4 < 2)
                reinterpret_cast<float*>(sp + SM_FG)[res * 128 + warp * 16 + q4 * 8 + g8] =
                    q4 ? (acc[0][2] + acc[1][2]) + acc[2][2] : (acc[0][0] + acc[1][0]) + acc[2][0];
        }
        named_sync(1, N_CONS);
        if (warp >= V_WARPS) {
            const float* f = reinterpret_cast<const float*>(sp + SM_FG) + (tid & 63);
            const float h = bf16r(bf16r(silu_f(bf16r(f[0] + f[64]))) * bf16r(f[128] + f[192]));
            ll_store(g_x + (cta - CL_FFN * CL) * 64 + (tid & 63), __float_as_uint(h) | tag);
        }
    }

    if (warp < V_WARPS) {
        const uint32_t rdst = mapa(sb + SM_OP + rank * 128 + (q4 * 8 + g8) * 4, warp), rbar = mapa(bar + BAR_O, warp);
#pragma unroll 1
        for (int hh = 0; hh < n_heads; hh++) {
            float oacc[2][2][4] = {};
#pragma unroll 2
            for (int u = hh * HEAD_TILES; u < (hh + 1) * HEAD_TILES; u++) {
                const int pos = pos_v + u, slot = pos & (N_SLOT - 1);
                uint32_t ta = sb + SM_RING + slot * TILE_BYTES + off_v, tc = ta ^ 32;
                asm volatile("" : "+r"(ta), "+r"(tc));
                const uint32_t pa = sb + SM_P + (u * 32 + 2 * q4) * 2;
                const uint32_t b0 = lds32(pa), b1 = lds32(pa + 16), b2 = lds32(pa + 32), b3 = lds32(pa + 48);
                mbar_wait(bar_full + slot * 8, (pos >> 4) & 1);
                uint32_t a[4][4];
                ldsm_x4_t(a[0], ta);
                ldsm_x4_t(a[1], tc);
                ldsm_x4_t(a[2], ta + PIECE_BYTES);
                ldsm_x4_t(a[3], tc + PIECE_BYTES);
                mma_bf16(oacc[0][0], a[0], b0, b1);
                mma_bf16(oacc[1][0], a[1], b0, b1);
                mma_bf16(oacc[0][1], a[2], b2, b3);
                mma_bf16(oacc[1][1], a[3], b2, b3);
                __syncwarp();
                if (lane == 0) mbar_arrive_n(bar_empty + slot * 8, RELEASE / V_WARPS);
            }
            const float v = pick4(oacc[0][0][0] + oacc[0][1][0], oacc[0][0][2] + oacc[0][1][2],
                                  oacc[1][0][0] + oacc[1][1][0], oacc[1][0][2] + oacc[1][1][2], q4);
            st_async(rdst + hh * 1024, v, rbar + hh * 8);
        }
    }
    if (!owner) return;

    {
        constexpr int P0 = POS_K2 + 4 * HEAD_TILES;
        const uint32_t rdst = mapa(sb + SM_FG + (rank * 2 + (warp >> 2)) * 64 + g8 * 8, warp & 3);
        const uint32_t rbar = mapa(bar + BAR_G, warp & 3);
        const uint32_t va = sb + SM_OV + ((warp >> 2) * 48 + 2 * q4) * 2, tw = sb + SM_RING + off_w;
        named_sync(8, N_CONS + N_GATHER);
        auto send = [&](const float (&acc)[3][4], uint32_t dst, uint32_t mb) {
            if (q4 == 0) st_async2(dst, (acc[0][0] + acc[1][0]) + acc[2][0], (acc[0][2] + acc[1][2]) + acc[2][2], mb);
        };
        float acc[3][4] = {};
#pragma unroll 1
        for (int i = 0; i < 6; i++) {
            const int slot = (P0 + i) & (N_SLOT - 1);
            uint32_t b[3][2];
#pragma unroll
            for (int k = 0; k < 3; k++) { b[k][0] = lds32(va + i * 192 + k * 32); b[k][1] = lds32(va + i * 192 + k * 32 + 16); }
            mbar_wait(bar_full + slot * 8, ((P0 + i) >> 4) & 1);
#pragma unroll
            for (int k = 0; k < 3; k++) {
                uint32_t a[4];
                ldsm_x4_t(a, tw + slot * TILE_BYTES + k * 2048);
                mma_bf16(acc[k], a, b[k][0], b[k][1]);
            }
            if (i == 1) {
                send(acc, rdst, rbar);
#pragma unroll
                for (int k = 0; k < 3; k++) acc[k][0] = acc[k][1] = acc[k][2] = acc[k][3] = 0.f;
            }
        }
        uint32_t ae[LATE_EARLY + 1][3][4];
#pragma unroll
        for (int i = 0; i < LATE_EARLY; i++) {
            const int slot = (P0 + 6 + i) & (N_SLOT - 1);
            mbar_wait(bar_full + slot * 8, ((P0 + 6 + i) >> 4) & 1);
#pragma unroll
            for (int k = 0; k < 3; k++) ldsm_x4_t(ae[i][k], tw + slot * TILE_BYTES + k * 2048);
        }
        uint32_t da = rdst + (SM_FS - SM_FG), ba = rbar + (BAR_S - BAR_G);
        asm volatile("" : "+r"(da), "+r"(ba));
        named_sync(3, N_CONS + N_GATHER);
        uint32_t b[4][3][2];
#pragma unroll
        for (int i = 0; i < 4; i++)
#pragma unroll
            for (int k = 0; k < 3; k++) { b[i][k][0] = lds32(va + (6 + i) * 192 + k * 32); b[i][k][1] = lds32(va + (6 + i) * 192 + k * 32 + 16); }
#pragma unroll
        for (int i = 0; i < LATE_EARLY; i++)
#pragma unroll
            for (int k = 0; k < 3; k++) mma_bf16(acc[k], ae[i][k], b[i][k][0], b[i][k][1]);
#pragma unroll
        for (int i = LATE_EARLY; i < 4; i++) {
            const int slot = (P0 + 6 + i) & (N_SLOT - 1);
            mbar_wait(bar_full + slot * 8, ((P0 + 6 + i) >> 4) & 1);
            uint32_t a[3][4];
#pragma unroll
            for (int k = 0; k < 3; k++) ldsm_x4_t(a[k], tw + slot * TILE_BYTES + k * 2048);
#pragma unroll
            for (int k = 0; k < 3; k++) mma_bf16(acc[k], a[k], b[i][k][0], b[i][k][1]);
        }
        send(acc, da, ba);
    }
}

typedef CUresult (*EncodeTiledFn)(CUtensorMap*, CUtensorMapDataType, cuuint32_t, void*, const cuuint64_t*,
                                  const cuuint64_t*, const cuuint32_t*, const cuuint32_t*, CUtensorMapInterleave,
                                  CUtensorMapSwizzle, CUtensorMapL2promotion, CUtensorMapFloatOOBfill);

void encode_map(EncodeTiledFn fn, CUtensorMap* m, const void* base, cuuint64_t rows, cuuint64_t cols, cuuint32_t b1, cuuint32_t b2) {
    const cuuint64_t dims[3] = {64, cols / 64, rows};
    const cuuint64_t strides[2] = {128, cols * 2};
    const cuuint32_t box[3] = {64, b1, b2};
    const cuuint32_t estr[3] = {1, 1, 1};
    fn(m, CU_TENSOR_MAP_DATA_TYPE_BFLOAT16, 3, const_cast<void*>(base), dims, strides, box, estr,
       CU_TENSOR_MAP_INTERLEAVE_NONE, CU_TENSOR_MAP_SWIZZLE_128B, CU_TENSOR_MAP_L2_PROMOTION_NONE,
       CU_TENSOR_MAP_FLOAT_OOB_FILL_NONE);
}

}

extern "C" void kernel_launch(void* const* d_in, const int* in_sizes, int n_in, void* d_out, int out_size) {
    (void)in_sizes; (void)n_in; (void)out_size;
    static EncodeTiledFn encode = nullptr;
    static double pace_scale = 1.0;
    static void* scratch = nullptr;
    if (!encode) {
        int dev = 0, mem_khz = 0, bus_bits = 0;
        cudaGetDevice(&dev);
        cudaDeviceGetAttribute(&mem_khz, cudaDevAttrMemoryClockRate, dev);
        cudaDeviceGetAttribute(&bus_bits, cudaDevAttrGlobalMemoryBusWidth, dev);
        const double peak_gbs = 2.0 * mem_khz * 1e-6 * bus_bits / 8.0;
        if (peak_gbs > 0.0) pace_scale = PACE_REF_GBS / peak_gbs;
        void* fn = nullptr;
        cudaDriverEntryPointQueryResult qr;
        cudaGetDriverEntryPoint("cuTensorMapEncodeTiled", &fn, cudaEnableDefault, &qr);
        encode = reinterpret_cast<EncodeTiledFn>(fn);
        cudaFuncSetAttribute(fused_decode_kernel, cudaFuncAttributeMaxDynamicSharedMemorySize, SM_ALLOC);
        cudaGetSymbolAddress(&scratch, g_scratch);
    }
    CUtensorMap tm_k, tm_v, tm_wq, tm_w1, tm_w3, tm_wo, tm_w2;
    encode_map(encode, &tm_k, d_in[1], (cuuint64_t)N_HEAD * SEQ, D_HEAD, 3, 32);
    encode_map(encode, &tm_v, d_in[2], (cuuint64_t)N_HEAD * SEQ, D_HEAD, 3, 32);
    encode_map(encode, &tm_wq, d_in[3], D_MODEL, N_HEAD * D_HEAD, 3, 16);
    encode_map(encode, &tm_w1, d_in[6], D_MODEL, D_FF, 1, 96);
    encode_map(encode, &tm_w3, d_in[7], D_MODEL, D_FF, 1, 96);
    encode_map(encode, &tm_wo, d_in[4], N_HEAD * D_HEAD, D_MODEL, 1, 96);
    encode_map(encode, &tm_w2, d_in[8], D_FF, D_MODEL, 1, 96);
    Params prm;
    prm.x = static_cast<const __nv_bfloat16*>(d_in[0]);
    prm.out = static_cast<__nv_bfloat16*>(d_out);
    prm.k = static_cast<const __nv_bfloat16*>(d_in[1]) + (size_t)(SEQ - WIN) * D_HEAD;
    prm.scratch = static_cast<uint32_t*>(scratch);
    auto step = [&](double pace, double bytes, int pieces) { return (uint16_t)(8.0 * pace * pace_scale * bytes / (128.0 * TILE_BYTES) / pieces); };
    const double b_wq = 2.0 * D_MODEL * N_HEAD * D_HEAD;
    const double b_mid = 4.0 * N_HEAD * WIN * D_HEAD - 2.0 * N_CTA * TILE_BYTES + 4.0 * D_MODEL * D_FF;
    const double b_tail = 2.0 * D_MODEL * (D_FF + N_HEAD * D_HEAD);
    prm.step_wq2 = step(PACE_HEAD, b_wq, 10);
    prm.step_wq3 = step(PACE_HEAD, b_wq, 15);
    prm.step_own = step(PACE_MID, b_mid, 4 * HEAD_TILES - 2);
    prm.step_ffn = step(PACE_MID, b_mid, 4 * HEAD_TILES - 2 + W_TILES);
    prm.step_tri = step(PACE_MID, b_mid, 6 * HEAD_TILES - 2);
    prm.step_tail = step(PACE_TAIL, b_tail, TAIL_TILES);
    prm.late = (uint16_t)(4096.0 * PACE_LATE / PACE_MID + 0.5);
    prm.pad = 0;
    fused_decode_kernel<<<N_CTA, N_THREADS, SM_ALLOC, cudaStreamPerThread>>>(prm, tm_wq, tm_w1, tm_w3, tm_k, tm_v, tm_wo, tm_w2);
}
```

```cpp
#include <cuda_runtime.h>
#include <cuda_bf16.h>
#include <cuda.h>
#include <stdint.h>

namespace {

constexpr int D_MODEL = 640;
constexpr int N_HEAD = 32;
constexpr int D_HEAD = 192;
constexpr int SEQ = 32768;
constexpr int WIN = 4096;
constexpr int D_FF = 1536;

constexpr int CL = 8;
constexpr int N_CL = 15;
constexpr int N_CTA = CL * N_CL;
constexpr int CL_FFN = 1, CL_TRI = CL_FFN + 3, CL_OWN = CL_TRI + 2;
constexpr int TILE_BYTES = 12288;
constexpr int PIECE_BYTES = TILE_BYTES / 2;
constexpr int N_SLOT = 16;
constexpr int HEAD_TILES = WIN / CL / 32;
constexpr int W_TILES = 14;
constexpr int TAIL_TILES = 10;
constexpr int POS_K2 = 5, POS_K3 = 8;

constexpr int N_CONS_WARPS = 8;
constexpr int N_CONS = N_CONS_WARPS * 32;
constexpr int N_GATHER = 128;
constexpr int N_THREADS = N_CONS + 64 + N_GATHER;
constexpr int V_WARPS = 6;
constexpr int RELEASE = 24;

constexpr double PACE_HEAD = 490, PACE_MID = 479, PACE_LATE = 495, PACE_TAIL = 478, PACE_REF_GBS = 3352.32;
constexpr int START_DELAY = 120;
constexpr int WINDOW_OWN = 5, WINDOW_FFN = 6, WINDOW_FAST = 8;
constexpr int SLIP = 50;
constexpr int GATE_EARLY = 4;
constexpr int LATE_EARLY = 2;
constexpr int GATE_LATE = 3;

constexpr unsigned SPIN_LIMIT = 1u << 22;

constexpr int SM_RING = 0;
constexpr int SM_BAR = N_SLOT * TILE_BYTES;
constexpr int BAR_FULL = 0, BAR_EMPTY = 128, BAR_GO = 256, BAR_Q = 272, BAR_ML = 280, BAR_O = 288, BAR_G = 312, BAR_S = 320, BAR_X = 328,
              BAR_READY = 336;
constexpr int SM_T0 = SM_BAR + 448, SM_EPOCH = SM_BAR + 452;
constexpr int SM_XN = SM_BAR + 512;
constexpr int SM_Q = SM_XN + 1408;
constexpr int SM_ST = SM_Q + 1152;
constexpr int SM_ML = SM_ST + 256;
constexpr int SM_P = SM_ML + 256;
constexpr int SM_QP = SM_P + 3072;
constexpr int SM_OP = SM_QP + 12288;
constexpr int SM_OV = SM_OP + 3072;
constexpr int SM_FG = SM_OV + 1920;
constexpr int SM_FS = SM_FG + 1024;
constexpr int SM_ALLOC = SM_FS + 1024 + 1024;

constexpr int XO_H = 32;
constexpr int XO_END = XO_H + D_FF + N_HEAD * D_HEAD;
__device__ __align__(128) uint32_t g_scratch[XO_END];

__device__ __forceinline__ uint32_t smem_u32(const void* p) { return (uint32_t)__cvta_generic_to_shared(p); }

__device__ __forceinline__ void mbar_init(uint32_t bar, uint32_t cnt) {
    asm volatile("mbarrier.init.shared::cta.b64 [%0], %1;" ::"r"(bar), "r"(cnt) : "memory");
}
__device__ __forceinline__ void mbar_expect_tx(uint32_t bar, uint32_t bytes) {
    asm volatile("mbarrier.arrive.expect_tx.shared::cta.b64 _, [%0], %1;" ::"r"(bar), "r"(bytes) : "memory");
}
__device__ __forceinline__ void mbar_arrive(uint32_t bar) {
    asm volatile("mbarrier.arrive.shared::cta.b64 _, [%0];" ::"r"(bar) : "memory");
}
__device__ __forceinline__ void mbar_wait(uint32_t bar, uint32_t parity) {
    asm volatile(
        "{\n.reg .pred p, q;\n.reg .u32 n;\n"
        "mov.u32 n, 0;\n"
        "WAIT_LOOP:\n"
        "add.u32 n, n, 1;\n"
        "setp.lt.u32 q, n, %2;\n"
        "mbarrier.try_wait.parity.shared::cta.b64 p, [%0], %1;\n"
        "and.pred q, q, !p;\n"
        "@q bra WAIT_LOOP;\n}"
        ::"r"(bar), "r"(parity), "n"(SPIN_LIMIT) : "memory");
}
__device__ __forceinline__ void named_sync(int id, int n) {
    asm volatile("bar.sync %0, %1;" ::"r"(id), "r"(n) : "memory");
}
__device__ __forceinline__ void named_arrive(int id, int n) {
    asm volatile("bar.arrive %0, %1;" ::"r"(id), "r"(n) : "memory");
}
__device__ __forceinline__ uint64_t stream_policy() {
    uint64_t pol;
    asm volatile("createpolicy.fractional.L2::evict_first.b64 %0, 1.0;" : "=l"(pol));
    return pol;
}
__device__ __forceinline__ void bulk_load(uint32_t dst, const void* src, uint32_t bytes, uint32_t bar, uint64_t pol) {
    asm volatile("cp.async.bulk.shared::cluster.global.mbarrier::complete_tx::bytes.L2::cache_hint [%0], [%1], %2, [%3], %4;"
                 ::"r"(dst), "l"(src), "r"(bytes), "r"(bar), "l"(pol) : "memory");
}
__device__ __forceinline__ void tma_3d(uint32_t dst, const CUtensorMap* tm, int c0, int c1, int c2, uint32_t bar, uint64_t pol) {
    asm volatile("cp.async.bulk.tensor.3d.shared::cluster.global.mbarrier::complete_tx::bytes.L2::cache_hint [%0], [%1, {%3, %4, %5}], [%2], %6;"
                 ::"r"(dst), "l"(tm), "r"(bar), "r"(c0), "r"(c1), "r"(c2), "l"(pol) : "memory");
}
__device__ __forceinline__ void prefetch_tmap(const CUtensorMap* tm) {
    asm volatile("prefetch.tensormap [%0];" ::"l"(tm) : "memory");
}
__device__ __forceinline__ void ldsm_x4(uint32_t (&r)[4], uint32_t addr) {
    asm volatile("ldmatrix.sync.aligned.m8n8.x4.shared.b16 {%0,%1,%2,%3}, [%4];"
                 : "=r"(r[0]), "=r"(r[1]), "=r"(r[2]), "=r"(r[3]) : "r"(addr) : "memory");
}
__device__ __forceinline__ void ldsm_x4_t(uint32_t (&r)[4], uint32_t addr) {
    asm volatile("ldmatrix.sync.aligned.m8n8.x4.trans.shared.b16 {%0,%1,%2,%3}, [%4];"
                 : "=r"(r[0]), "=r"(r[1]), "=r"(r[2]), "=r"(r[3]) : "r"(addr) : "memory");
}
__device__ __forceinline__ void mma_bf16(float (&c)[4], const uint32_t (&a)[4], uint32_t b0, uint32_t b1) {
    asm volatile("mma.sync.aligned.m16n8k16.row.col.f32.bf16.bf16.f32 {%0,%1,%2,%3}, {%4,%5,%6,%7}, {%8,%9}, {%0,%1,%2,%3};"
                 : "+f"(c[0]), "+f"(c[1]), "+f"(c[2]), "+f"(c[3])
                 : "r"(a[0]), "r"(a[1]), "r"(a[2]), "r"(a[3]), "r"(b0), "r"(b1));
}
__device__ __forceinline__ float bf16r(float v) {
    uint32_t p;
    asm("cvt.rn.bf16x2.f32 %0, %1, %2;" : "=r"(p) : "f"(v), "f"(0.f));
    return __uint_as_float(p);
}
__device__ __forceinline__ uint32_t lds32(uint32_t addr) {
    uint32_t v;
    asm volatile("ld.shared.b32 %0, [%1];" : "=r"(v) : "r"(addr) : "memory");
    return v;
}
__device__ __forceinline__ float bf_lo(uint32_t v) { return __uint_as_float(v << 16); }
__device__ __forceinline__ float bf_hi(uint32_t v) { return __uint_as_float(v & 0xffff0000u); }
__device__ __forceinline__ uint32_t pack_bf16(float lo, float hi) {
    const __nv_bfloat162 p = __floats2bfloat162_rn(lo, hi);
    return *reinterpret_cast<const uint32_t*>(&p);
}
__device__ __forceinline__ uint32_t now_ns() {
    unsigned long long t;
    asm volatile("mov.u64 %0, %%globaltimer;" : "=l"(t));
    return (uint32_t)t;
}

__device__ __forceinline__ void wait_until(uint32_t t_start, uint32_t deadline) {
    unsigned n = 0;
    while (now_ns() - t_start < deadline && ++n < SPIN_LIMIT) {}
}

__device__ __forceinline__ uint32_t ll_bad4(const uint4& v, uint32_t tag) {
    uint32_t lo, hi;
    asm("lop3.b32 %0, %1, %2, %3, 0x7E;" : "=r"(lo) : "r"(v.x), "r"(v.y), "r"(tag));
    asm("lop3.b32 %0, %1, %2, %3, 0x7E;" : "=r"(hi) : "r"(v.z), "r"(v.w), "r"(tag));
    return (lo | hi) & 3u;
}
__device__ __forceinline__ float ex2(float v) {
    float r;
    asm("ex2.approx.ftz.f32 %0, %1;" : "=f"(r) : "f"(v));
    return r;
}
__device__ __forceinline__ float rcp(float v) {
    float r;
    asm("rcp.approx.ftz.f32 %0, %1;" : "=f"(r) : "f"(v));
    return r;
}
constexpr float LOG2E = 1.4426950408889634f;
__device__ __forceinline__ void ll_store(uint32_t* p, uint32_t w) {
    asm volatile("st.relaxed.gpu.global.b32 [%0], %1;" ::"l"(p), "r"(w) : "memory");
}
__device__ __forceinline__ uint32_t ll_ld(const uint32_t* p) {
    uint32_t v;
    asm volatile("ld.relaxed.gpu.global.b32 %0, [%1];" : "=r"(v) : "l"(p) : "memory");
    return v;
}
__device__ __forceinline__ float pick4(float a, float b, float c, float d, int j) {
    const float lo = (j & 1) ? b : a, hi = (j & 1) ? d : c;
    return (j & 2) ? hi : lo;
}
__device__ __forceinline__ float silu_f(float v) { return v * rcp(1.f + ex2(-LOG2E * v)); }

__device__ __forceinline__ void mbar_arrive_n(uint32_t bar, uint32_t n) {
    asm volatile("mbarrier.arrive.shared::cta.b64 _, [%0], %1;" ::"r"(bar), "r"(n) : "memory");
}
__device__ __forceinline__ uint32_t mapa(uint32_t addr, uint32_t rank) {
    uint32_t d;
    asm("mapa.shared::cluster.u32 %0, %1, %2;" : "=r"(d) : "r"(addr), "r"(rank));
    return d;
}
__device__ __forceinline__ void st_async(uint32_t dst, float v, uint32_t bar) {
    asm volatile("st.async.weak.shared::cluster.mbarrier::complete_tx::bytes.f32 [%0], %1, [%2];" ::"r"(dst), "f"(v), "r"(bar) : "memory");
}
__device__ __forceinline__ void st_async2(uint32_t dst, float a, float b, uint32_t bar) {
    asm volatile("st.async.weak.shared::cluster.mbarrier::complete_tx::bytes.v2.f32 [%0], {%1, %2}, [%3];" ::"r"(dst), "f"(a), "f"(b), "r"(bar) : "memory");
}
__device__ __forceinline__ void cluster_arrive() { asm volatile("barrier.cluster.arrive.relaxed.aligned;" ::: "memory"); }
__device__ __forceinline__ void cluster_wait() { asm volatile("barrier.cluster.wait.aligned;" ::: "memory"); }
__device__ __forceinline__ void ll_ld4_if(uint4& v, const uint32_t* p, uint32_t cond) {
    asm volatile("{\n.reg .pred p;\nsetp.ne.u32 p, %5, 0;\n@p ld.relaxed.gpu.global.v4.b32 {%0,%1,%2,%3}, [%4];\n}"
                 : "+r"(v.x), "+r"(v.y), "+r"(v.z), "+r"(v.w) : "l"(p), "r"(cond) : "memory");
}
__device__ __forceinline__ float lds_f(uint32_t addr) { return __uint_as_float(lds32(addr)); }
__device__ __forceinline__ float lds_colsum(uint32_t addr) {
    float v[8];
#pragma unroll
    for (int i = 0; i < 8; i++) v[i] = lds_f(addr + i * 128);
    const float s = ((v[0] + v[1]) + (v[2] + v[3])) + ((v[4] + v[5]) + (v[6] + v[7]));
    return s + __shfl_xor_sync(0xffffffffu, s, 16);
}

constexpr uint32_t FIRST_MUL = 257, FIRST_MASK = 0x7807;
__device__ __forceinline__ int pair_head(int cl, int j) { return 2 * cl + j; }
__device__ __forceinline__ int third_head(int cl) { return 2 * N_CL + cl - CL_TRI; }
__device__ __forceinline__ int head_at(int cl, int hh, int tri) { return (hh & tri) ? third_head(cl) : pair_head(cl, hh >> tri); }
__device__ __forceinline__ int tail_row(int rank, int i) {
    if (i < 2) return i * 768 + rank * 96;
    const int j = 4 * (i - 2) + (rank >> 1), q = rank & 1;
    return D_FF + (2 * (j & 15) + (j >> 4)) * D_HEAD + q * 96;
}

struct Params {
    const __nv_bfloat16* x;
    __nv_bfloat16* out;
    const __nv_bfloat16* k;
    uint32_t* scratch;
    uint16_t step_wq2, step_wq3, step_own, step_ffn, step_tri, step_tail, late, pad;
};
static_assert(sizeof(Params) == 48, "Params must fill the rest of the first parameter line");

__global__ void __cluster_dims__(CL, 1, 1) __launch_bounds__(N_THREADS, 1)
fused_decode_kernel(const Params prm, const __grid_constant__ CUtensorMap tm_wq, const __grid_constant__ CUtensorMap tm_w1,
                    const __grid_constant__ CUtensorMap tm_w3, const __grid_constant__ CUtensorMap tm_k,
                    const __grid_constant__ CUtensorMap tm_v, const __grid_constant__ CUtensorMap tm_wo,
                    const __grid_constant__ CUtensorMap tm_w2) {
    extern __shared__ uint8_t smem_raw[];
    asm volatile("{\n.reg .pred p;\nsetp.lt.u32 p, %1, %2;\n@p prefetch.global.L2 [%0];\n}"
                 ::"l"(reinterpret_cast<const char*>(prm.k) + (size_t)(((blockIdx.x * FIRST_MUL) & FIRST_MASK) * (TILE_BYTES / 32) + threadIdx.x) * 32),
                   "r"(threadIdx.x), "n"(TILE_BYTES / 32) : "memory");
    const uint32_t sb = (smem_u32(smem_raw) + 1023u) & ~1023u;
    uint8_t* sp = smem_raw + (sb - smem_u32(smem_raw));
    const uint32_t bar = sb + SM_BAR;
    const uint32_t bar_full = bar + BAR_FULL, bar_empty = bar + BAR_EMPTY;

    const int tid = threadIdx.x;
    const int cta = blockIdx.x, cl = blockIdx.x / CL, rank = blockIdx.x % CL;
    const int tri = cl >= CL_TRI && cl < CL_OWN;
    const int pos_k = tri ? POS_K3 : POS_K2;
    volatile uint32_t* t_first = reinterpret_cast<volatile uint32_t*>(sp + SM_T0);
    if (tid == N_CONS) {
        const __nv_bfloat16* k0 = prm.k + (uint32_t)(pair_head(cl, 0) * SEQ + rank * 32) * (size_t)D_HEAD;
#pragma unroll
        for (int u = 1; u >= 0; u--) {
            const uint32_t fb = bar_full + (pos_k + u) * 8;
            mbar_init(fb, 1);
            asm volatile("fence.mbarrier_init.release.cluster;" ::: "memory");
            mbar_expect_tx(fb, TILE_BYTES);
            bulk_load(sb + SM_RING + (pos_k + u) * TILE_BYTES, k0 + u * (CL * 32 * D_HEAD), TILE_BYTES, fb, stream_policy());
            if (u == 1) *t_first = now_ns();
        }
    }
    if (tid == N_CONS + 32) prefetch_tmap(&tm_wq);
    const int warp = __shfl_sync(0xffffffffu, tid >> 5, 0), lane = tid & 31;
    const bool owner = cl < CL_FFN || cl >= CL_OWN, ffn = !owner && !tri;
    const int oc = cl < CL_FFN ? cl : cl - (CL_OWN - CL_FFN);
    const int n_heads = 2 + tri;
    const int pos_w = pos_k + n_heads * HEAD_TILES;
    const int pos_v = pos_w + (ffn ? W_TILES : 0);
    const int pos_t = pos_v + n_heads * HEAD_TILES;
    uint32_t* const g_epoch = prm.scratch;
    uint32_t* const g_x = prm.scratch + XO_H;
    const int n_start = owner ? N_THREADS : N_THREADS - 96;

    if (warp == N_CONS_WARPS) {
        if (lane == 0) {
#pragma unroll
            for (int i = 2; i < N_SLOT; i++) mbar_init(bar_full + ((pos_k + i) & (N_SLOT - 1)) * 8, 1);
            mbar_init(bar + BAR_READY, 1);
            asm volatile("fence.mbarrier_init.release.cluster;" ::: "memory");
        }
        __syncwarp();
        named_arrive(6, n_start);
        cluster_arrive();
        if (lane == 0) {
            const uint64_t pol = stream_policy();
            const uint32_t t_start = *t_first;
            uint32_t deadline = START_DELAY * 8;
            {
                const uint32_t step = tri ? prm.step_wq3 : prm.step_wq2;
#pragma unroll 1
                for (int p = 0; p < 10 + 5 * tri; p++) {
                    const uint32_t fb = bar_full + (p >> 1) * 8;
                    if (!(p & 1)) mbar_expect_tx(fb, p == 14 ? PIECE_BYTES : TILE_BYTES);
                    const int h = p < 10 ? pair_head(cl, rank >> 2) : third_head(cl);
                    const int row = p < 10 ? p * 64 + (rank & 3) * 16 : (p - 10) * 128 + rank * 16;
                    wait_until(t_start, deadline >> 3);
                    tma_3d(sb + SM_RING + p * PIECE_BYTES, &tm_wq, 0, h * 3, row, fb, pol);
                    deadline += step;
                }
            }
            mbar_wait(bar + BAR_READY, 0);
            uint32_t step = owner ? prm.step_own : (tri ? prm.step_tri : prm.step_ffn);
            int window = owner ? WINDOW_OWN : (tri ? WINDOW_FAST : WINDOW_FFN);
            const int pos_end = pos_t + (owner ? TAIL_TILES : 0);
            const int pos_late = pos_t - (owner ? 16 : (tri ? 24 : 20));
#pragma unroll 1
            for (int pos = pos_k + 2; pos < pos_end; pos++) {
                const int slot = pos & (N_SLOT - 1);
                const CUtensorMap* tm;
                int c1 = 0, row;
                if (pos >= pos_t) {
                    step = prm.step_tail;
                    window = WINDOW_FAST;
                    row = tail_row(rank, pos - pos_t);
                    tm = row < D_FF ? &tm_w2 : &tm_wo;
                    if (row >= D_FF) row -= D_FF;
                    c1 = oc;
                } else if (pos >= pos_w && pos < pos_v) {
                    const bool up = pos >= pos_w + W_TILES / 2;
                    tm = up ? &tm_w3 : &tm_w1;
                    c1 = cta - CL_FFN * CL;
                    row = (pos - pos_w - (up ? W_TILES / 2 : 0)) * 96;
                } else {
                    const int u = pos - (pos < pos_w ? pos_k : pos_v), hh = u >> 4;
                    tm = pos < pos_w ? &tm_k : &tm_v;
                    row = head_at(cl, hh, tri) * SEQ + (SEQ - WIN) + rank * 32 + (u & 15) * (CL * 32);
                }
                if (pos >= N_SLOT) mbar_wait(bar_empty + slot * 8, ((pos >> 4) - 1) & 1);
                if (pos >= pos_k + 2 + window) mbar_wait(bar_full + ((pos - window) & (N_SLOT - 1)) * 8, ((pos - window) >> 4) & 1);
                deadline = max(deadline, (now_ns() - t_start - SLIP) << 3);
                mbar_expect_tx(bar_full + slot * 8, TILE_BYTES);
                wait_until(t_start, deadline >> 3);
                tma_3d(sb + SM_RING + slot * TILE_BYTES, tm, 0, c1, row, bar_full + slot * 8, pol);
                deadline += step;
                if (pos == pos_late) step = step * prm.late >> 12;
                if (pos == pos_t - GATE_EARLY) mbar_arrive(bar + BAR_GO);
                if (pos == pos_t + GATE_LATE) mbar_arrive(bar + BAR_GO + 8);
            }
        }
        return;
    }

    if (warp > N_CONS_WARPS + 2 && !owner) return;
    if (tid == N_CONS + 32) {
#pragma unroll
        for (int i = 0; i < N_SLOT; i++) mbar_init(bar_empty + i * 8, RELEASE);
        asm volatile("fence.mbarrier_init.release.cluster;" ::: "memory");
    }
    if (tid == N_CONS + 64) {
#pragma unroll
        for (int i = BAR_GO; i <= BAR_X; i += 8) mbar_init(bar + i, 1);
        mbar_expect_tx(bar + BAR_X, D_MODEL * 2 + 4);
        mbar_expect_tx(bar + BAR_Q, (1 + tri) * CL * D_HEAD * 4);
        mbar_expect_tx(bar + BAR_ML, n_heads * CL * 8);
#pragma unroll
        for (int i = BAR_O; i <= BAR_S; i += 8) mbar_expect_tx(bar + i, 1024);
        asm volatile("fence.mbarrier_init.release.cluster;" ::: "memory");
    }
    __syncwarp();
    cluster_arrive();
    float* sst = reinterpret_cast<float*>(sp + SM_ST);
    if (tid < 8) *reinterpret_cast<uint2*>(sp + SM_XN + D_MODEL * 2 + tid * 8) = make_uint2(0u, 0u);
    if (rank == CL - 1 && warp >= V_WARPS && warp < N_CONS_WARPS) {
        if (warp == V_WARPS) {
            const uint32_t ep = ll_ld(g_epoch);
            cluster_wait();
            if (lane < CL) st_async(mapa(sb + SM_EPOCH, lane), __uint_as_float(ep), mapa(bar + BAR_X, lane));
        } else {
            uint2 u[5];
#pragma unroll
            for (int i = 0; i < 5; i++) u[i] = *reinterpret_cast<const uint2*>(prm.x + i * 128 + lane * 4);
            float s = 0.f;
#pragma unroll
            for (int i = 0; i < 5; i++) s += (bf_lo(u[i].x) + bf_hi(u[i].x)) + (bf_lo(u[i].y) + bf_hi(u[i].y));
#pragma unroll
            for (int o = 16; o > 0; o >>= 1) s += __shfl_xor_sync(0xffffffffu, s, o);
            const float mean = s * (1.f / D_MODEL);
            s = 0.f;
#pragma unroll
            for (int i = 0; i < 5; i++) {
                const float a = bf_lo(u[i].x) - mean, b = bf_hi(u[i].x) - mean, c = bf_lo(u[i].y) - mean, d = bf_hi(u[i].y) - mean;
                s += fmaf(a, a, b * b) + fmaf(c, c, d * d);
            }
#pragma unroll
            for (int o = 16; o > 0; o >>= 1) s += __shfl_xor_sync(0xffffffffu, s, o);
            const float mean_b = bf16r(mean);
            float den;
            asm("sqrt.approx.f32 %0, %1;" : "=f"(den) : "f"(bf16r(bf16r(s * (1.f / D_MODEL)) + 1e-5f)));
            const float inv = rcp(bf16r(den));
#pragma unroll
            for (int i = 0; i < 5; i++) {
                const uint32_t d0 = pack_bf16(bf_lo(u[i].x) - mean_b, bf_hi(u[i].x) - mean_b);
                const uint32_t d1 = pack_bf16(bf_lo(u[i].y) - mean_b, bf_hi(u[i].y) - mean_b);
                u[i] = make_uint2(pack_bf16(bf_lo(d0) * inv, bf_hi(d0) * inv), pack_bf16(bf_lo(d1) * inv, bf_hi(d1) * inv));
            }
            cluster_wait();
#pragma unroll 1
            for (int d = 0; d < CL; d++) {
                const uint32_t dst = mapa(sb + SM_XN + lane * 8, d), mb = mapa(bar + BAR_X, d);
#pragma unroll
                for (int i = 0; i < 5; i++) st_async2(dst + i * 256, __uint_as_float(u[i].x), __uint_as_float(u[i].y), mb);
            }
        }
        __syncwarp();
    }
    if (warp == N_CONS_WARPS + 1 && rank < V_WARPS) {
        ll_store(g_x + D_FF + pair_head(cl, 1) * D_HEAD + rank * 32 + lane, 0u);
    } else if (warp > N_CONS_WARPS && (!owner || warp == N_CONS_WARPS + 1)) {
        named_arrive(6, n_start);
        return;
    }
    named_sync(6, n_start);
    if (tid == 0) mbar_arrive(bar + BAR_READY);
    mbar_wait(bar + BAR_X, 0);
    const uint32_t epoch = lds32(sb + SM_EPOCH);
    const uint32_t tag = 1u + (epoch & 1u);

    if (warp == N_CONS_WARPS + 1) {
        const bool fin = owner && rank < 4;
        const int col = oc * 64 + rank * 16 + (lane & 1) * 8 + ((lane >> 1) & 7);
        uint16_t* const out = reinterpret_cast<uint16_t*>(prm.out) + col;
        mbar_wait(bar + BAR_ML, 0);
        uint32_t xv = 0;
        if (fin) xv = reinterpret_cast<const uint16_t*>(prm.x)[col];
        float wv;
        {
            const uint32_t ma = sb + SM_ML + (lane < n_heads * CL ? lane : 0) * 8;
            const float mi = lds_f(ma);
            float m = fmaxf(mi, __shfl_xor_sync(0xffffffffu, mi, 1));
            m = fmaxf(m, __shfl_xor_sync(0xffffffffu, m, 2));
            m = fmaxf(m, __shfl_xor_sync(0xffffffffu, m, 4));
            const float ei = ex2((mi - m) * LOG2E);
            float den = ei * lds_f(ma + 4);
            den += __shfl_xor_sync(0xffffffffu, den, 1);
            den += __shfl_xor_sync(0xffffffffu, den, 2);
            den += __shfl_xor_sync(0xffffffffu, den, 4);
            wv = ei * rcp(den);
        }
#pragma unroll 1
        for (int hh = 0; hh < n_heads; hh++) {
            float w[CL];
#pragma unroll
            for (int s = 0; s < CL; s++) w[s] = __shfl_sync(0xffffffffu, wv, hh * CL + s);
            uint32_t* dst = g_x + D_FF + head_at(cl, hh, tri) * D_HEAD + rank * 32 + lane;
            const uint32_t src = sb + SM_OP + hh * 1024 + lane * 4;
            mbar_wait(bar + BAR_O + hh * 8, 0);
            float v[CL];
#pragma unroll
            for (int s = 0; s < CL; s++) v[s] = lds_f(src + s * 128);
            const float o = (fmaf(w[1], v[1], w[0] * v[0]) + fmaf(w[3], v[3], w[2] * v[2])) +
                            (fmaf(w[5], v[5], w[4] * v[4]) + fmaf(w[7], v[7], w[6] * v[6]));
            ll_store(dst, __float_as_uint(bf16r(o)) | tag);
        }
        if (fin) {
            mbar_wait(bar + BAR_G, 0);
            const uint32_t g = pack_bf16(silu_f(bf16r(lds_colsum(sb + SM_FG + lane * 4))), 0.f);
            asm volatile("{\n.reg .pred p;\nsetp.eq.u32 p, %2, 0;\n@p st.relaxed.gpu.global.b32 [%0], %1;\n}" ::"l"(g_epoch), "r"(epoch + 1u), "r"(oc + rank + lane) : "memory");
            mbar_wait(bar + BAR_S, 0);
            uint32_t res = pack_bf16(lds_colsum(sb + SM_FS + lane * 4), 0.f);
            asm("mul.rn.bf16x2 %0, %0, %1;" : "+r"(res) : "r"(g));
            asm("add.rn.bf16x2 %0, %0, %1;" : "+r"(res) : "r"(xv));
            if (lane < 16) *out = (uint16_t)res;
        }
        return;
    }
    if (warp >= N_CONS_WARPS + 2) {
        const int gw = warp - (N_CONS_WARPS + 2);
        mbar_wait(bar + BAR_GO, 0);
#pragma unroll 1
        for (int round = 0; round < 2; round++) {
            const int i0 = round * 4 + 2 + gw;
            const uint32_t* src0 = g_x + tail_row(rank, i0) + lane * 4;
            const uint32_t* src1 = g_x + tail_row(rank, gw) + lane * 4;
            if (round == 1) {
                named_arrive(8, N_CONS + N_GATHER);
                mbar_wait(bar + BAR_GO + 8, 0);
                mbar_wait(bar_full + ((pos_t + GATE_LATE) & (N_SLOT - 1)) * 8, ((pos_t + GATE_LATE) >> 4) & 1);
            }
            uint4 v0 = make_uint4(0u, 0u, 0u, 0u), v1 = v0;
            const bool second = round == 0 && gw < 2 && lane < 24;
            uint32_t miss0 = lane < 24, miss1 = second;
            unsigned n = 0;
#pragma unroll 1
            while (true) {
                ll_ld4_if(v0, src0, miss0);
                ll_ld4_if(v1, src1, miss1);
                if (ll_bad4(v0, tag) == 0) miss0 = 0;
                if (ll_bad4(v1, tag) == 0) miss1 = 0;
                if (__all_sync(0xffffffffu, (miss0 | miss1) == 0) || ++n > SPIN_LIMIT) break;
            }
            if (lane < 24)
                *reinterpret_cast<uint2*>(sp + SM_OV + i0 * 192 + lane * 8) = make_uint2(__byte_perm(v0.x, v0.y, 0x7632), __byte_perm(v0.z, v0.w, 0x7632));
            if (second)
                *reinterpret_cast<uint2*>(sp + SM_OV + gw * 192 + lane * 8) = make_uint2(__byte_perm(v1.x, v1.y, 0x7632), __byte_perm(v1.z, v1.w, 0x7632));
        }
        named_arrive(3, N_CONS + N_GATHER);
        return;
    }


    const int q4 = lane & 3, g8 = lane >> 2;
    const int rowT = (lane & 7) + ((lane >> 4) << 3), hiT = (lane >> 3) & 1;
    const uint32_t off_v = ((3 * rowT + (warp >> 1)) * 128 + ((hiT ^ ((3 * rowT + (warp >> 1)) & 7)) << 4)) ^ ((warp & 1) << 6);

    if (warp < V_WARPS) {
#pragma unroll 1
        for (int part = 0; part <= tri; part++) {
            const uint32_t xa = sb + SM_XN + ((part ? rank * 16 - 1280 : (rank & 3) * 16) + 2 * q4) * 2, xs = 128 << part;
            float acc[2][4] = {};
#pragma unroll 1
            for (int p = part * 10; p < 10 + part * 5; p++) {
                const uint32_t b0 = lds32(xa + p * xs), b1 = lds32(xa + p * xs + 16);
                mbar_wait(bar_full + (p >> 1) * 8, 0);
                uint32_t a[4];
                ldsm_x4_t(a, sb + SM_RING + p * PIECE_BYTES + off_v);
                mma_bf16(acc[0], a, b0, b1);
                ldsm_x4_t(a, sb + SM_RING + p * PIECE_BYTES + (off_v ^ 32));
                mma_bf16(acc[1], a, b0, b1);
                __syncwarp();
                if (lane == 0) mbar_arrive_n(bar_empty + (p >> 1) * 8, p == 14 ? RELEASE / V_WARPS : RELEASE / V_WARPS / 2);
            }
            const float v = pick4(acc[0][0], acc[0][2], acc[1][0], acc[1][2], q4);
            const uint32_t dst = sb + SM_QP + ((part * CL + rank) * D_HEAD + warp * 32 + q4 * 8 + g8) * 4;
#pragma unroll
            for (int d = 0; d < CL; d++) st_async(mapa(dst, d), v, mapa(bar + BAR_Q, d));
        }
        mbar_wait(bar + BAR_Q, 0);
        const float* qp = reinterpret_cast<const float*>(sp + SM_QP) + tid;
        __nv_bfloat16* qs = reinterpret_cast<__nv_bfloat16*>(sp + SM_Q) + tid;
        qs[0] = __float2bfloat16_rn((qp[0] + qp[192]) + (qp[384] + qp[576]));
        qs[(tri + 1) * D_HEAD] = __float2bfloat16_rn((qp[768] + qp[960]) + (qp[1152] + qp[1344]));
        if (tri) {
            qp += CL * D_HEAD;
            qs[D_HEAD] = __float2bfloat16_rn(((qp[0] + qp[192]) + (qp[384] + qp[576])) + ((qp[768] + qp[960]) + (qp[1152] + qp[1344])));
        }
    }
    named_sync(1, N_CONS);

    {
        const int rowN = (lane & 7) + (((lane >> 3) & 1) << 3), hiN = lane >> 4;
#pragma unroll 1
        for (int hh = 0; hh < n_heads; hh++) {
            float s0 = 0.f, s1 = 0.f;
#pragma unroll 1
            for (int i = 0; i < 2; i++) {
                const int u = hh * HEAD_TILES + i * 8 + warp, pos = pos_k + u, slot = pos & (N_SLOT - 1);
                mbar_wait(bar_full + slot * 8, (pos >> 4) & 1);
                const uint32_t tb = sb + SM_RING + slot * TILE_BYTES;
                float acc[2][2][4] = {};
#pragma unroll 1
                for (int j = 0; j < 3; j++) {
                    const int swz = u < 2 ? 0 : (3 * rowN + j) & 7;
                    const uint32_t oj = tb + (3 * rowN + j) * 128 + ((hiN ^ swz) << 4);
                    const uint32_t qa = sb + SM_Q + (hh * D_HEAD + j * 64 + 2 * q4) * 2;
#pragma unroll
                    for (int k = 0; k < 4; k++) {
                        const uint32_t b0 = lds32(qa + k * 32), b1 = lds32(qa + k * 32 + 16);
                        uint32_t a[4];
                        ldsm_x4(a, oj ^ (k << 5));
                        mma_bf16(acc[0][k & 1], a, b0, b1);
                        ldsm_x4(a, (oj + PIECE_BYTES) ^ (k << 5));
                        mma_bf16(acc[1][k & 1], a, b0, b1);
                    }
                }
                __syncwarp();
                if (lane == 0) mbar_arrive_n(bar_empty + slot * 8, RELEASE);
                const float raw = pick4(acc[0][0][0] + acc[0][1][0], acc[0][0][2] + acc[0][1][2],
                                        acc[1][0][0] + acc[1][1][0], acc[1][0][2] + acc[1][1][2], q4);
                s0 = s1;
                s1 = bf16r(bf16r(raw) * 0.07216878364870323f);
            }
            float m = fmaxf(s0, s1);
#pragma unroll
            for (int o = 16; o > 0; o >>= 1) m = fmaxf(m, __shfl_xor_sync(0xffffffffu, m, o));
            if (lane == 0) sst[hh * 8 + warp] = m;
            named_sync(1, N_CONS);
#pragma unroll
            for (int w = 0; w < 8; w++) m = fmaxf(m, sst[hh * 8 + w]);
            const float p0 = ex2((s0 - m) * LOG2E), p1 = ex2((s1 - m) * LOG2E);
            float l = p0 + p1;
#pragma unroll
            for (int o = 16; o > 0; o >>= 1) l += __shfl_xor_sync(0xffffffffu, l, o);
            if (lane == 0) sst[24 + hh * 8 + warp] = l;
            __nv_bfloat16* ps = reinterpret_cast<__nv_bfloat16*>(sp + SM_P) + hh * 512 + warp * 32 + q4 * 8 + g8;
            ps[0] = __float2bfloat16_rn(p0);
            ps[256] = __float2bfloat16_rn(p1);
        }
        named_sync(1, N_CONS);
        if (warp == 7 && lane < n_heads * CL && (lane & 7) < V_WARPS) {
            const float* st = sst + (lane & 24);
            float m = st[0], l = st[24];
#pragma unroll
            for (int w = 1; w < 8; w++) { m = fmaxf(m, st[w]); l += st[24 + w]; }
            st_async2(mapa(sb + SM_ML + ((lane & 24) + rank) * 8, lane & 7), m, l, mapa(bar + BAR_ML, lane & 7));
        }
    }

    const uint32_t off_w = (warp >> 2) * PIECE_BYTES + rowT * 128 + (((((warp & 3) << 1) | hiT) ^ (rowT & 7)) << 4);

    if (ffn) {
#pragma unroll 1
        for (int res = 0; res < 2; res++) {
            float acc[3][4] = {};
#pragma unroll 1
            for (int i = 0; i < W_TILES / 2; i++) {
                const int pos = pos_w + res * (W_TILES / 2) + i, slot = pos & (N_SLOT - 1);
                const uint32_t xa = sb + SM_XN + (i * 96 + (warp >> 2) * 48 + 2 * q4) * 2;
                mbar_wait(bar_full + slot * 8, (pos >> 4) & 1);
#pragma unroll
                for (int k = 0; k < 3; k++) {
                    uint32_t a[4];
                    ldsm_x4_t(a, sb + SM_RING + slot * TILE_BYTES + off_w + k * 2048);
                    mma_bf16(acc[k], a, lds32(xa + k * 32), lds32(xa + k * 32 + 16));
                }
                __syncwarp();
                if (lane == 0) mbar_arrive_n(bar_empty + slot * 8, RELEASE / N_CONS_WARPS);
            }
            if (q4 < 2)
                reinterpret_cast<float*>(sp + SM_FG)[res * 128 + warp * 16 + q4 * 8 + g8] =
                    q4 ? (acc[0][2] + acc[1][2]) + acc[2][2] : (acc[0][0] + acc[1][0]) + acc[2][0];
        }
        named_sync(1, N_CONS);
        if (warp >= V_WARPS) {
            const float* f = reinterpret_cast<const float*>(sp + SM_FG) + (tid & 63);
            const float h = bf16r(bf16r(silu_f(bf16r(f[0] + f[64]))) * bf16r(f[128] + f[192]));
            ll_store(g_x + (cta - CL_FFN * CL) * 64 + (tid & 63), __float_as_uint(h) | tag);
        }
    }

    if (warp < V_WARPS) {
        const uint32_t rdst = mapa(sb + SM_OP + rank * 128 + (q4 * 8 + g8) * 4, warp), rbar = mapa(bar + BAR_O, warp);
#pragma unroll 1
        for (int hh = 0; hh < n_heads; hh++) {
            float oacc[2][2][4] = {};
#pragma unroll 2
            for (int u = hh * HEAD_TILES; u < (hh + 1) * HEAD_TILES; u++) {
                const int pos = pos_v + u, slot = pos & (N_SLOT - 1);
                uint32_t ta = sb + SM_RING + slot * TILE_BYTES + off_v, tc = ta ^ 32;
                asm volatile("" : "+r"(ta), "+r"(tc));
                const uint32_t pa = sb + SM_P + (u * 32 + 2 * q4) * 2;
                const uint32_t b0 = lds32(pa), b1 = lds32(pa + 16), b2 = lds32(pa + 32), b3 = lds32(pa + 48);
                mbar_wait(bar_full + slot * 8, (pos >> 4) & 1);
                uint32_t a[4][4];
                ldsm_x4_t(a[0], ta);
                ldsm_x4_t(a[1], tc);
                ldsm_x4_t(a[2], ta + PIECE_BYTES);
                ldsm_x4_t(a[3], tc + PIECE_BYTES);
                mma_bf16(oacc[0][0], a[0], b0, b1);
                mma_bf16(oacc[1][0], a[1], b0, b1);
                mma_bf16(oacc[0][1], a[2], b2, b3);
                mma_bf16(oacc[1][1], a[3], b2, b3);
                __syncwarp();
                if (lane == 0) mbar_arrive_n(bar_empty + slot * 8, RELEASE / V_WARPS);
            }
            const float v = pick4(oacc[0][0][0] + oacc[0][1][0], oacc[0][0][2] + oacc[0][1][2],
                                  oacc[1][0][0] + oacc[1][1][0], oacc[1][0][2] + oacc[1][1][2], q4);
            st_async(rdst + hh * 1024, v, rbar + hh * 8);
        }
    }
    if (!owner) return;

    {
        constexpr int P0 = POS_K2 + 4 * HEAD_TILES;
        const uint32_t rdst = mapa(sb + SM_FG + (rank * 2 + (warp >> 2)) * 64 + g8 * 8, warp & 3);
        const uint32_t rbar = mapa(bar + BAR_G, warp & 3);
        const uint32_t va = sb + SM_OV + ((warp >> 2) * 48 + 2 * q4) * 2, tw = sb + SM_RING + off_w;
        named_sync(8, N_CONS + N_GATHER);
        auto send = [&](const float (&acc)[3][4], uint32_t dst, uint32_t mb) {
            if (q4 == 0) st_async2(dst, (acc[0][0] + acc[1][0]) + acc[2][0], (acc[0][2] + acc[1][2]) + acc[2][2], mb);
        };
        float acc[3][4] = {};
#pragma unroll 1
        for (int i = 0; i < 6; i++) {
            const int slot = (P0 + i) & (N_SLOT - 1);
            uint32_t b[3][2];
#pragma unroll
            for (int k = 0; k < 3; k++) { b[k][0] = lds32(va + i * 192 + k * 32); b[k][1] = lds32(va + i * 192 + k * 32 + 16); }
            mbar_wait(bar_full + slot * 8, ((P0 + i) >> 4) & 1);
#pragma unroll
            for (int k = 0; k < 3; k++) {
                uint32_t a[4];
                ldsm_x4_t(a, tw + slot * TILE_BYTES + k * 2048);
                mma_bf16(acc[k], a, b[k][0], b[k][1]);
            }
            if (i == 1) {
                send(acc, rdst, rbar);
#pragma unroll
                for (int k = 0; k < 3; k++) acc[k][0] = acc[k][1] = acc[k][2] = acc[k][3] = 0.f;
            }
        }
        uint32_t ae[LATE_EARLY + 1][3][4];
#pragma unroll
        for (int i = 0; i < LATE_EARLY; i++) {
            const int slot = (P0 + 6 + i) & (N_SLOT - 1);
            mbar_wait(bar_full + slot * 8, ((P0 + 6 + i) >> 4) & 1);
#pragma unroll
            for (int k = 0; k < 3; k++) ldsm_x4_t(ae[i][k], tw + slot * TILE_BYTES + k * 2048);
        }
        uint32_t da = rdst + (SM_FS - SM_FG), ba = rbar + (BAR_S - BAR_G);
        asm volatile("" : "+r"(da), "+r"(ba));
        named_sync(3, N_CONS + N_GATHER);
        uint32_t b[4][3][2];
#pragma unroll
        for (int i = 0; i < 4; i++)
#pragma unroll
            for (int k = 0; k < 3; k++) { b[i][k][0] = lds32(va + (6 + i) * 192 + k * 32); b[i][k][1] = lds32(va + (6 + i) * 192 + k * 32 + 16); }
#pragma unroll
        for (int i = 0; i < LATE_EARLY; i++)
#pragma unroll
            for (int k = 0; k < 3; k++) mma_bf16(acc[k], ae[i][k], b[i][k][0], b[i][k][1]);
#pragma unroll
        for (int i = LATE_EARLY; i < 4; i++) {
            const int slot = (P0 + 6 + i) & (N_SLOT - 1);
            mbar_wait(bar_full + slot * 8, ((P0 + 6 + i) >> 4) & 1);
            uint32_t a[3][4];
#pragma unroll
            for (int k = 0; k < 3; k++) ldsm_x4_t(a[k], tw + slot * TILE_BYTES + k * 2048);
#pragma unroll
            for (int k = 0; k < 3; k++) mma_bf16(acc[k], a[k], b[i][k][0], b[i][k][1]);
        }
        send(acc, da, ba);
    }
}

typedef CUresult (*EncodeTiledFn)(CUtensorMap*, CUtensorMapDataType, cuuint32_t, void*, const cuuint64_t*,
                                  const cuuint64_t*, const cuuint32_t*, const cuuint32_t*, CUtensorMapInterleave,
                                  CUtensorMapSwizzle, CUtensorMapL2promotion, CUtensorMapFloatOOBfill);

void encode_map(EncodeTiledFn fn, CUtensorMap* m, const void* base, cuuint64_t rows, cuuint64_t cols, cuuint32_t b1, cuuint32_t b2) {
    const cuuint64_t dims[3] = {64, cols / 64, rows};
    const cuuint64_t strides[2] = {128, cols * 2};
    const cuuint32_t box[3] = {64, b1, b2};
    const cuuint32_t estr[3] = {1, 1, 1};
    fn(m, CU_TENSOR_MAP_DATA_TYPE_BFLOAT16, 3, const_cast<void*>(base), dims, strides, box, estr,
       CU_TENSOR_MAP_INTERLEAVE_NONE, CU_TENSOR_MAP_SWIZZLE_128B, CU_TENSOR_MAP_L2_PROMOTION_NONE,
       CU_TENSOR_MAP_FLOAT_OOB_FILL_NONE);
}

}

extern "C" void kernel_launch(void* const* d_in, const int* in_sizes, int n_in, void* d_out, int out_size) {
    (void)in_sizes; (void)n_in; (void)out_size;
    static EncodeTiledFn encode = nullptr;
    static double pace_scale = 1.0;
    static void* scratch = nullptr;
    if (!encode) {
        int dev = 0, mem_khz = 0, bus_bits = 0;
        cudaGetDevice(&dev);
        cudaDeviceGetAttribute(&mem_khz, cudaDevAttrMemoryClockRate, dev);
        cudaDeviceGetAttribute(&bus_bits, cudaDevAttrGlobalMemoryBusWidth, dev);
        const double peak_gbs = 2.0 * mem_khz * 1e-6 * bus_bits / 8.0;
        if (peak_gbs > 0.0) pace_scale = PACE_REF_GBS / peak_gbs;
        void* fn = nullptr;
        cudaDriverEntryPointQueryResult qr;
        cudaGetDriverEntryPoint("cuTensorMapEncodeTiled", &fn, cudaEnableDefault, &qr);
        encode = reinterpret_cast<EncodeTiledFn>(fn);
        cudaFuncSetAttribute(fused_decode_kernel, cudaFuncAttributeMaxDynamicSharedMemorySize, SM_ALLOC);
        cudaGetSymbolAddress(&scratch, g_scratch);
    }
    CUtensorMap tm_k, tm_v, tm_wq, tm_w1, tm_w3, tm_wo, tm_w2;
    encode_map(encode, &tm_k, d_in[1], (cuuint64_t)N_HEAD * SEQ, D_HEAD, 3, 32);
    encode_map(encode, &tm_v, d_in[2], (cuuint64_t)N_HEAD * SEQ, D_HEAD, 3, 32);
    encode_map(encode, &tm_wq, d_in[3], D_MODEL, N_HEAD * D_HEAD, 3, 16);
    encode_map(encode, &tm_w1, d_in[6], D_MODEL, D_FF, 1, 96);
    encode_map(encode, &tm_w3, d_in[7], D_MODEL, D_FF, 1, 96);
    encode_map(encode, &tm_wo, d_in[4], N_HEAD * D_HEAD, D_MODEL, 1, 96);
    encode_map(encode, &tm_w2, d_in[8], D_FF, D_MODEL, 1, 96);
    Params prm;
    prm.x = static_cast<const __nv_bfloat16*>(d_in[0]);
    prm.out = static_cast<__nv_bfloat16*>(d_out);
    prm.k = static_cast<const __nv_bfloat16*>(d_in[1]) + (size_t)(SEQ - WIN) * D_HEAD;
    prm.scratch = static_cast<uint32_t*>(scratch);
    auto step = [&](double pace, double bytes, int pieces) { return (uint16_t)(8.0 * pace * pace_scale * bytes / (128.0 * TILE_BYTES) / pieces); };
    const double b_wq = 2.0 * D_MODEL * N_HEAD * D_HEAD;
    const double b_mid = 4.0 * N_HEAD * WIN * D_HEAD - 2.0 * N_CTA * TILE_BYTES + 4.0 * D_MODEL * D_FF;
    const double b_tail = 2.0 * D_MODEL * (D_FF + N_HEAD * D_HEAD);
    prm.step_wq2 = step(PACE_HEAD, b_wq, 10);
    prm.step_wq3 = step(PACE_HEAD, b_wq, 15);
    prm.step_own = step(PACE_MID, b_mid, 4 * HEAD_TILES - 2);
    prm.step_ffn = step(PACE_MID, b_mid, 4 * HEAD_TILES - 2 + W_TILES);
    prm.step_tri = step(PACE_MID, b_mid, 6 * HEAD_TILES - 2);
    prm.step_tail = step(PACE_TAIL, b_tail, TAIL_TILES);
    prm.late = (uint16_t)(4096.0 * PACE_LATE / PACE_MID + 0.5);
    prm.pad = 0;
    fused_decode_kernel<<<N_CTA, N_THREADS, SM_ALLOC, cudaStreamPerThread>>>(prm, tm_wq, tm_w1, tm_w3, tm_k, tm_v, tm_wo, tm_w2);
}
```

```cpp
#include <cuda_runtime.h>
#include <cuda_bf16.h>
#include <cuda.h>
#include <stdint.h>

namespace {

constexpr int D_MODEL = 640;
constexpr int N_HEAD = 32;
constexpr int D_HEAD = 192;
constexpr int SEQ = 32768;
constexpr int WIN = 4096;
constexpr int D_FF = 1536;

constexpr int CL = 8;
constexpr int N_CL = 15;
constexpr int N_CTA = CL * N_CL;
constexpr int CL_FFN = 1, CL_TRI = CL_FFN + 3, CL_OWN = CL_TRI + 2;
constexpr int TILE_BYTES = 12288;
constexpr int PIECE_BYTES = TILE_BYTES / 2;
constexpr int N_SLOT = 16;
constexpr int HEAD_TILES = WIN / CL / 32;
constexpr int W_TILES = 14;
constexpr int TAIL_TILES = 10;
constexpr int POS_K2 = 5, POS_K3 = 8;

constexpr int N_CONS_WARPS = 8;
constexpr int N_CONS = N_CONS_WARPS * 32;
constexpr int N_GATHER = 128;
constexpr int N_THREADS = N_CONS + 64 + N_GATHER;
constexpr int V_WARPS = 6;
constexpr int RELEASE = 24;

constexpr double PACE_HEAD = 490, PACE_MID = 479, PACE_LATE = 495, PACE_TAIL = 482, PACE_REF_GBS = 3352.32;
constexpr int START_DELAY = 140;
constexpr int WINDOW_OWN = 5, WINDOW_FFN = 6, WINDOW_FAST = 8;
constexpr int SLIP = 50;
constexpr int GATE_EARLY = 4;
constexpr int GATE_LATE = 3;

constexpr unsigned SPIN_LIMIT = 1u << 22;

constexpr int SM_RING = 0;
constexpr int SM_BAR = N_SLOT * TILE_BYTES;
constexpr int BAR_FULL = 0, BAR_EMPTY = 128, BAR_GO = 256, BAR_Q = 272, BAR_ML = 280, BAR_O = 288, BAR_G = 312, BAR_S = 320, BAR_X = 328,
              BAR_HALF = 336, BAR_READY = 368;
constexpr int SM_T0 = SM_BAR + 448, SM_EPOCH = SM_BAR + 452;
constexpr int SM_XN = SM_BAR + 512;
constexpr int SM_Q = SM_XN + 1408;
constexpr int SM_ST = SM_Q + 1152;
constexpr int SM_ML = SM_ST + 256;
constexpr int SM_P = SM_ML + 256;
constexpr int SM_QP = SM_P + 3072;
constexpr int SM_OP = SM_QP + 12288;
constexpr int SM_OV = SM_OP + 3072;
constexpr int SM_FG = SM_OV + 1920;
constexpr int SM_FS = SM_FG + 1024;
constexpr int SM_ALLOC = SM_FS + 1024 + 1024;

constexpr int XO_H = 32;
constexpr int XO_END = XO_H + D_FF + N_HEAD * D_HEAD;
__device__ __align__(128) uint32_t g_scratch[XO_END];

__device__ __forceinline__ uint32_t smem_u32(const void* p) { return (uint32_t)__cvta_generic_to_shared(p); }

__device__ __forceinline__ void mbar_init(uint32_t bar, uint32_t cnt) {
    asm volatile("mbarrier.init.shared::cta.b64 [%0], %1;" ::"r"(bar), "r"(cnt) : "memory");
}
__device__ __forceinline__ void mbar_expect_tx(uint32_t bar, uint32_t bytes) {
    asm volatile("mbarrier.arrive.expect_tx.shared::cta.b64 _, [%0], %1;" ::"r"(bar), "r"(bytes) : "memory");
}
__device__ __forceinline__ void mbar_arrive(uint32_t bar) {
    asm volatile("mbarrier.arrive.shared::cta.b64 _, [%0];" ::"r"(bar) : "memory");
}
__device__ __forceinline__ void mbar_wait(uint32_t bar, uint32_t parity) {
    asm volatile(
        "{\n.reg .pred p, q;\n.reg .u32 n;\n"
        "mov.u32 n, 0;\n"
        "WAIT_LOOP:\n"
        "add.u32 n, n, 1;\n"
        "setp.lt.u32 q, n, %2;\n"
        "mbarrier.try_wait.parity.shared::cta.b64 p, [%0], %1;\n"
        "and.pred q, q, !p;\n"
        "@q bra WAIT_LOOP;\n}"
        ::"r"(bar), "r"(parity), "n"(SPIN_LIMIT) : "memory");
}
__device__ __forceinline__ void named_sync(int id, int n) {
    asm volatile("bar.sync %0, %1;" ::"r"(id), "r"(n) : "memory");
}
__device__ __forceinline__ void named_arrive(int id, int n) {
    asm volatile("bar.arrive %0, %1;" ::"r"(id), "r"(n) : "memory");
}
__device__ __forceinline__ uint64_t stream_policy() {
    uint64_t pol;
    asm volatile("createpolicy.fractional.L2::evict_first.b64 %0, 1.0;" : "=l"(pol));
    return pol;
}
__device__ __forceinline__ void bulk_load(uint32_t dst, const void* src, uint32_t bytes, uint32_t bar, uint64_t pol) {
    asm volatile("cp.async.bulk.shared::cluster.global.mbarrier::complete_tx::bytes.L2::cache_hint [%0], [%1], %2, [%3], %4;"
                 ::"r"(dst), "l"(src), "r"(bytes), "r"(bar), "l"(pol) : "memory");
}
__device__ __forceinline__ void tma_3d(uint32_t dst, const CUtensorMap* tm, int c0, int c1, int c2, uint32_t bar, uint64_t pol) {
    asm volatile("cp.async.bulk.tensor.3d.shared::cluster.global.mbarrier::complete_tx::bytes.L2::cache_hint [%0], [%1, {%3, %4, %5}], [%2], %6;"
                 ::"r"(dst), "l"(tm), "r"(bar), "r"(c0), "r"(c1), "r"(c2), "l"(pol) : "memory");
}
__device__ __forceinline__ void prefetch_tmap(const CUtensorMap* tm) {
    asm volatile("prefetch.tensormap [%0];" ::"l"(tm) : "memory");
}
__device__ __forceinline__ void ldsm_x4(uint32_t (&r)[4], uint32_t addr) {
    asm volatile("ldmatrix.sync.aligned.m8n8.x4.shared.b16 {%0,%1,%2,%3}, [%4];"
                 : "=r"(r[0]), "=r"(r[1]), "=r"(r[2]), "=r"(r[3]) : "r"(addr) : "memory");
}
__device__ __forceinline__ void ldsm_x4_t(uint32_t (&r)[4], uint32_t addr) {
    asm volatile("ldmatrix.sync.aligned.m8n8.x4.trans.shared.b16 {%0,%1,%2,%3}, [%4];"
                 : "=r"(r[0]), "=r"(r[1]), "=r"(r[2]), "=r"(r[3]) : "r"(addr) : "memory");
}
__device__ __forceinline__ void mma_bf16(float (&c)[4], const uint32_t (&a)[4], uint32_t b0, uint32_t b1) {
    asm volatile("mma.sync.aligned.m16n8k16.row.col.f32.bf16.bf16.f32 {%0,%1,%2,%3}, {%4,%5,%6,%7}, {%8,%9}, {%0,%1,%2,%3};"
                 : "+f"(c[0]), "+f"(c[1]), "+f"(c[2]), "+f"(c[3])
                 : "r"(a[0]), "r"(a[1]), "r"(a[2]), "r"(a[3]), "r"(b0), "r"(b1));
}
__device__ __forceinline__ float bf16r(float v) {
    uint32_t p;
    asm("cvt.rn.bf16x2.f32 %0, %1, %2;" : "=r"(p) : "f"(v), "f"(0.f));
    return __uint_as_float(p);
}
__device__ __forceinline__ uint32_t lds32(uint32_t addr) {
    uint32_t v;
    asm volatile("ld.shared.b32 %0, [%1];" : "=r"(v) : "r"(addr) : "memory");
    return v;
}
__device__ __forceinline__ float bf_lo(uint32_t v) { return __uint_as_float(v << 16); }
__device__ __forceinline__ float bf_hi(uint32_t v) { return __uint_as_float(v & 0xffff0000u); }
__device__ __forceinline__ uint32_t pack_bf16(float lo, float hi) {
    const __nv_bfloat162 p = __floats2bfloat162_rn(lo, hi);
    return *reinterpret_cast<const uint32_t*>(&p);
}
__device__ __forceinline__ uint32_t now_ns() {
    unsigned long long t;
    asm volatile("mov.u64 %0, %%globaltimer;" : "=l"(t));
    return (uint32_t)t;
}

__device__ __forceinline__ void wait_until(uint32_t t_start, uint32_t deadline) {
    unsigned n = 0;
    while (now_ns() - t_start < deadline && ++n < SPIN_LIMIT) {}
}

__device__ __forceinline__ uint32_t ll_bad4(const uint4& v, uint32_t tag) {
    uint32_t lo, hi;
    asm("lop3.b32 %0, %1, %2, %3, 0x7E;" : "=r"(lo) : "r"(v.x), "r"(v.y), "r"(tag));
    asm("lop3.b32 %0, %1, %2, %3, 0x7E;" : "=r"(hi) : "r"(v.z), "r"(v.w), "r"(tag));
    return (lo | hi) & 3u;
}
__device__ __forceinline__ float ex2(float v) {
    float r;
    asm("ex2.approx.ftz.f32 %0, %1;" : "=f"(r) : "f"(v));
    return r;
}
__device__ __forceinline__ float rcp(float v) {
    float r;
    asm("rcp.approx.ftz.f32 %0, %1;" : "=f"(r) : "f"(v));
    return r;
}
constexpr float LOG2E = 1.4426950408889634f;
__device__ __forceinline__ void ll_store(uint32_t* p, uint32_t w) {
    asm volatile("st.relaxed.gpu.global.b32 [%0], %1;" ::"l"(p), "r"(w) : "memory");
}
__device__ __forceinline__ uint32_t ll_ld(const uint32_t* p) {
    uint32_t v;
    asm volatile("ld.relaxed.gpu.global.b32 %0, [%1];" : "=r"(v) : "l"(p) : "memory");
    return v;
}
__device__ __forceinline__ float pick4(float a, float b, float c, float d, int j) {
    const float lo = (j & 1) ? b : a, hi = (j & 1) ? d : c;
    return (j & 2) ? hi : lo;
}
__device__ __forceinline__ float silu_f(float v) { return v * rcp(1.f + ex2(-LOG2E * v)); }

__device__ __forceinline__ void mbar_arrive_n(uint32_t bar, uint32_t n) {
    asm volatile("mbarrier.arrive.shared::cta.b64 _, [%0], %1;" ::"r"(bar), "r"(n) : "memory");
}
__device__ __forceinline__ uint32_t mapa(uint32_t addr, uint32_t rank) {
    uint32_t d;
    asm("mapa.shared::cluster.u32 %0, %1, %2;" : "=r"(d) : "r"(addr), "r"(rank));
    return d;
}
__device__ __forceinline__ void st_async(uint32_t dst, float v, uint32_t bar) {
    asm volatile("st.async.weak.shared::cluster.mbarrier::complete_tx::bytes.f32 [%0], %1, [%2];" ::"r"(dst), "f"(v), "r"(bar) : "memory");
}
__device__ __forceinline__ void st_async2(uint32_t dst, float a, float b, uint32_t bar) {
    asm volatile("st.async.weak.shared::cluster.mbarrier::complete_tx::bytes.v2.f32 [%0], {%1, %2}, [%3];" ::"r"(dst), "f"(a), "f"(b), "r"(bar) : "memory");
}
__device__ __forceinline__ void cluster_arrive() { asm volatile("barrier.cluster.arrive.relaxed.aligned;" ::: "memory"); }
__device__ __forceinline__ void cluster_wait() { asm volatile("barrier.cluster.wait.aligned;" ::: "memory"); }
__device__ __forceinline__ void ll_ld4_if(uint4& v, const uint32_t* p, uint32_t cond) {
    asm volatile("{\n.reg .pred p;\nsetp.ne.u32 p, %5, 0;\n@p ld.relaxed.gpu.global.v4.b32 {%0,%1,%2,%3}, [%4];\n}"
                 : "+r"(v.x), "+r"(v.y), "+r"(v.z), "+r"(v.w) : "l"(p), "r"(cond) : "memory");
}
__device__ __forceinline__ float lds_f(uint32_t addr) { return __uint_as_float(lds32(addr)); }
__device__ __forceinline__ float lds_colsum(uint32_t addr) {
    float v[8];
#pragma unroll
    for (int i = 0; i < 8; i++) v[i] = lds_f(addr + i * 128);
    const float s = ((v[0] + v[1]) + (v[2] + v[3])) + ((v[4] + v[5]) + (v[6] + v[7]));
    return s + __shfl_xor_sync(0xffffffffu, s, 16);
}

constexpr uint32_t FIRST_MUL = 257, FIRST_MASK = 0x7807;
__device__ __forceinline__ int pair_head(int cl, int j) { return 2 * cl + j; }
__device__ __forceinline__ int third_head(int cl) { return 2 * N_CL + cl - CL_TRI; }
__device__ __forceinline__ int head_at(int cl, int hh, int tri) { return (hh & tri) ? third_head(cl) : pair_head(cl, hh >> tri); }
__device__ __forceinline__ int tail_row(int rank, int i) {
    if (i < 2) return i * 768 + rank * 96;
    const int j = 4 * (i - 2) + (rank >> 1), q = rank & 1;
    return D_FF + (2 * (j & 15) + (j >> 4)) * D_HEAD + q * 96;
}

struct Params {
    const __nv_bfloat16* x;
    __nv_bfloat16* out;
    const __nv_bfloat16* k;
    uint32_t* scratch;
    uint16_t step_wq2, step_wq3, step_own, step_ffn, step_tri, step_tail, late, pad;
};
static_assert(sizeof(Params) == 48, "Params must fill the rest of the first parameter line");

__global__ void __cluster_dims__(CL, 1, 1) __launch_bounds__(N_THREADS, 1)
fused_decode_kernel(const Params prm, const __grid_constant__ CUtensorMap tm_wq, const __grid_constant__ CUtensorMap tm_w1,
                    const __grid_constant__ CUtensorMap tm_w3, const __grid_constant__ CUtensorMap tm_k,
                    const __grid_constant__ CUtensorMap tm_v, const __grid_constant__ CUtensorMap tm_wo,
                    const __grid_constant__ CUtensorMap tm_w2) {
    extern __shared__ uint8_t smem_raw[];
    asm volatile("{\n.reg .pred p;\nsetp.lt.u32 p, %1, %2;\n@p prefetch.global.L2 [%0];\n}"
                 ::"l"(reinterpret_cast<const char*>(prm.k) + (size_t)(((blockIdx.x * FIRST_MUL) & FIRST_MASK) * (TILE_BYTES / 32) + threadIdx.x) * 32),
                   "r"(threadIdx.x), "n"(TILE_BYTES / 32) : "memory");
    const uint32_t sb = (smem_u32(smem_raw) + 1023u) & ~1023u;
    uint8_t* sp = smem_raw + (sb - smem_u32(smem_raw));
    const uint32_t bar = sb + SM_BAR;
    const uint32_t bar_full = bar + BAR_FULL, bar_empty = bar + BAR_EMPTY;

    const int tid = threadIdx.x;
    const int cta = blockIdx.x, cl = blockIdx.x / CL, rank = blockIdx.x % CL;
    const int tri = cl >= CL_TRI && cl < CL_OWN;
    const int pos_k = tri ? POS_K3 : POS_K2;
    volatile uint32_t* t_first = reinterpret_cast<volatile uint32_t*>(sp + SM_T0);
    if (tid == N_CONS) {
        const __nv_bfloat16* k0 = prm.k + (uint32_t)(pair_head(cl, 0) * SEQ + rank * 32) * (size_t)D_HEAD;
#pragma unroll
        for (int u = 1; u >= 0; u--) {
            const uint32_t fb = bar_full + (pos_k + u) * 8;
            mbar_init(fb, 1);
            asm volatile("fence.mbarrier_init.release.cluster;" ::: "memory");
            mbar_expect_tx(fb, TILE_BYTES);
            bulk_load(sb + SM_RING + (pos_k + u) * TILE_BYTES, k0 + u * (CL * 32 * D_HEAD), TILE_BYTES, fb, stream_policy());
            if (u == 1) *t_first = now_ns();
        }
    }
    if (tid == N_CONS + 32) prefetch_tmap(&tm_wq);
    const int warp = __shfl_sync(0xffffffffu, tid >> 5, 0), lane = tid & 31;
    const bool owner = cl < CL_FFN || cl >= CL_OWN, ffn = !owner && !tri;
    const int oc = cl < CL_FFN ? cl : cl - (CL_OWN - CL_FFN);
    const int n_heads = 2 + tri;
    const int pos_w = pos_k + n_heads * HEAD_TILES;
    const int pos_v = pos_w + (ffn ? W_TILES : 0);
    const int pos_t = pos_v + n_heads * HEAD_TILES;
    uint32_t* const g_epoch = prm.scratch;
    uint32_t* const g_x = prm.scratch + XO_H;
    const int n_start = owner ? N_THREADS : N_THREADS - 96;

    if (warp == N_CONS_WARPS) {
        if (lane == 0) {
#pragma unroll
            for (int i = 2; i < N_SLOT; i++) mbar_init(bar_full + ((pos_k + i) & (N_SLOT - 1)) * 8, 1);
            mbar_init(bar + BAR_READY, 1);
            asm volatile("fence.mbarrier_init.release.cluster;" ::: "memory");
        }
        __syncwarp();
        named_arrive(6, n_start);
        cluster_arrive();
        if (lane == 0) {
            const uint64_t pol = stream_policy();
            const uint32_t t_start = *t_first;
            uint32_t deadline = START_DELAY * 8;
            {
                const uint32_t step = tri ? prm.step_wq3 : prm.step_wq2;
#pragma unroll 1
                for (int p = 0; p < 10 + 5 * tri; p++) {
                    const uint32_t fb = bar_full + (p >> 1) * 8;
                    if (!(p & 1)) mbar_expect_tx(fb, p == 14 ? PIECE_BYTES : TILE_BYTES);
                    const int h = p < 10 ? pair_head(cl, rank >> 2) : third_head(cl);
                    const int row = p < 10 ? p * 64 + (rank & 3) * 16 : (p - 10) * 128 + rank * 16;
                    wait_until(t_start, deadline >> 3);
                    tma_3d(sb + SM_RING + p * PIECE_BYTES, &tm_wq, 0, h * 3, row, fb, pol);
                    deadline += step;
                }
            }
            mbar_wait(bar + BAR_READY, 0);
            uint32_t step = owner ? prm.step_own : (tri ? prm.step_tri : prm.step_ffn);
            int window = owner ? WINDOW_OWN : (tri ? WINDOW_FAST : WINDOW_FFN);
            const int pos_end = pos_t + (owner ? TAIL_TILES : 0);
            const int pos_late = pos_t - (owner ? 16 : (tri ? 24 : 20));
#pragma unroll 1
            for (int pos = pos_k + 2; pos < pos_end; pos++) {
                const int slot = pos & (N_SLOT - 1);
                const CUtensorMap* tm;
                int c1 = 0, row;
                if (pos >= pos_t) {
                    step = prm.step_tail;
                    window = WINDOW_FAST;
                    row = tail_row(rank, pos - pos_t);
                    tm = row < D_FF ? &tm_w2 : &tm_wo;
                    if (row >= D_FF) row -= D_FF;
                    c1 = oc;
                } else if (pos >= pos_w && pos < pos_v) {
                    const bool up = pos >= pos_w + W_TILES / 2;
                    tm = up ? &tm_w3 : &tm_w1;
                    c1 = cta - CL_FFN * CL;
                    row = (pos - pos_w - (up ? W_TILES / 2 : 0)) * 96;
                } else {
                    const int u = pos - (pos < pos_w ? pos_k : pos_v), hh = u >> 4;
                    tm = pos < pos_w ? &tm_k : &tm_v;
                    row = head_at(cl, hh, tri) * SEQ + (SEQ - WIN) + rank * 32 + (u & 15) * (CL * 32);
                }
                if (pos >= N_SLOT) mbar_wait(bar_empty + slot * 8, ((pos >> 4) - 1) & 1);
                if (pos >= pos_k + 2 + window) mbar_wait(bar_full + ((pos - window) & (N_SLOT - 1)) * 8, ((pos - window) >> 4) & 1);
                deadline = max(deadline, (now_ns() - t_start - SLIP) << 3);
                mbar_expect_tx(bar_full + slot * 8, pos >= pos_t + 6 ? PIECE_BYTES : TILE_BYTES);
                wait_until(t_start, deadline >> 3);
                tma_3d(sb + SM_RING + slot * TILE_BYTES, tm, 0, c1, row, bar_full + slot * 8, pol);
                if (pos >= pos_t)
                    tma_3d(sb + SM_RING + slot * TILE_BYTES + PIECE_BYTES, tm, 0, c1, row + 48,
                           pos >= pos_t + 6 ? bar + BAR_HALF + (pos - pos_t - 6) * 8 : bar_full + slot * 8, pol);
                deadline += step;
                if (pos == pos_late) step = step * prm.late >> 12;
                if (pos == pos_t - GATE_EARLY) mbar_arrive(bar + BAR_GO);
                if (pos == pos_t + GATE_LATE) mbar_arrive(bar + BAR_GO + 8);
            }
        }
        return;
    }

    if (warp > N_CONS_WARPS + 2 && !owner) return;
    if (tid == N_CONS + 32) {
#pragma unroll
        for (int i = 0; i < N_SLOT; i++) mbar_init(bar_empty + i * 8, RELEASE);
        asm volatile("fence.mbarrier_init.release.cluster;" ::: "memory");
    }
    if (tid == N_CONS + 64) {
#pragma unroll
        for (int i = BAR_GO; i < BAR_READY; i += 8) mbar_init(bar + i, 1);
#pragma unroll
        for (int i = BAR_HALF; i < BAR_READY; i += 8) mbar_expect_tx(bar + i, PIECE_BYTES);
        mbar_expect_tx(bar + BAR_X, D_MODEL * 2 + 4);
        mbar_expect_tx(bar + BAR_Q, (1 + tri) * CL * D_HEAD * 4);
        mbar_expect_tx(bar + BAR_ML, n_heads * CL * 8);
#pragma unroll
        for (int i = BAR_O; i <= BAR_S; i += 8) mbar_expect_tx(bar + i, 1024);
        asm volatile("fence.mbarrier_init.release.cluster;" ::: "memory");
    }
    __syncwarp();
    cluster_arrive();
    float* sst = reinterpret_cast<float*>(sp + SM_ST);
    if (tid < 8) *reinterpret_cast<uint2*>(sp + SM_XN + D_MODEL * 2 + tid * 8) = make_uint2(0u, 0u);
    if (rank == CL - 1 && warp >= V_WARPS && warp < N_CONS_WARPS) {
        if (warp == V_WARPS) {
            const uint32_t ep = ll_ld(g_epoch);
            cluster_wait();
            if (lane < CL) st_async(mapa(sb + SM_EPOCH, lane), __uint_as_float(ep), mapa(bar + BAR_X, lane));
        } else {
            uint2 u[5];
#pragma unroll
            for (int i = 0; i < 5; i++) u[i] = *reinterpret_cast<const uint2*>(prm.x + i * 128 + lane * 4);
            float s = 0.f;
#pragma unroll
            for (int i = 0; i < 5; i++) s += (bf_lo(u[i].x) + bf_hi(u[i].x)) + (bf_lo(u[i].y) + bf_hi(u[i].y));
#pragma unroll
            for (int o = 16; o > 0; o >>= 1) s += __shfl_xor_sync(0xffffffffu, s, o);
            const float mean = s * (1.f / D_MODEL);
            s = 0.f;
#pragma unroll
            for (int i = 0; i < 5; i++) {
                const float a = bf_lo(u[i].x) - mean, b = bf_hi(u[i].x) - mean, c = bf_lo(u[i].y) - mean, d = bf_hi(u[i].y) - mean;
                s += fmaf(a, a, b * b) + fmaf(c, c, d * d);
            }
#pragma unroll
            for (int o = 16; o > 0; o >>= 1) s += __shfl_xor_sync(0xffffffffu, s, o);
            const float mean_b = bf16r(mean);
            float den;
            asm("sqrt.approx.f32 %0, %1;" : "=f"(den) : "f"(bf16r(bf16r(s * (1.f / D_MODEL)) + 1e-5f)));
            const float inv = rcp(bf16r(den));
#pragma unroll
            for (int i = 0; i < 5; i++) {
                const uint32_t d0 = pack_bf16(bf_lo(u[i].x) - mean_b, bf_hi(u[i].x) - mean_b);
                const uint32_t d1 = pack_bf16(bf_lo(u[i].y) - mean_b, bf_hi(u[i].y) - mean_b);
                u[i] = make_uint2(pack_bf16(bf_lo(d0) * inv, bf_hi(d0) * inv), pack_bf16(bf_lo(d1) * inv, bf_hi(d1) * inv));
            }
            cluster_wait();
#pragma unroll 1
            for (int d = 0; d < CL; d++) {
                const uint32_t dst = mapa(sb + SM_XN + lane * 8, d), mb = mapa(bar + BAR_X, d);
#pragma unroll
                for (int i = 0; i < 5; i++) st_async2(dst + i * 256, __uint_as_float(u[i].x), __uint_as_float(u[i].y), mb);
            }
        }
        __syncwarp();
    }
    if (warp == N_CONS_WARPS + 1 && rank < V_WARPS) {
        ll_store(g_x + D_FF + pair_head(cl, 1) * D_HEAD + rank * 32 + lane, 0u);
    } else if (warp > N_CONS_WARPS && (!owner || warp == N_CONS_WARPS + 1)) {
        named_arrive(6, n_start);
        return;
    }
    named_sync(6, n_start);
    if (tid == 0) mbar_arrive(bar + BAR_READY);
    mbar_wait(bar + BAR_X, 0);
    const uint32_t epoch = lds32(sb + SM_EPOCH);
    const uint32_t tag = 1u + (epoch & 1u);

    if (warp == N_CONS_WARPS + 1) {
        const bool fin = owner && rank < 4;
        const int col = oc * 64 + rank * 16 + (lane & 1) * 8 + ((lane >> 1) & 7);
        uint16_t* const out = reinterpret_cast<uint16_t*>(prm.out) + col;
        mbar_wait(bar + BAR_ML, 0);
        uint32_t xv = 0;
        if (fin) xv = reinterpret_cast<const uint16_t*>(prm.x)[col];
        float wv;
        {
            const uint32_t ma = sb + SM_ML + (lane < n_heads * CL ? lane : 0) * 8;
            const float mi = lds_f(ma);
            float m = fmaxf(mi, __shfl_xor_sync(0xffffffffu, mi, 1));
            m = fmaxf(m, __shfl_xor_sync(0xffffffffu, m, 2));
            m = fmaxf(m, __shfl_xor_sync(0xffffffffu, m, 4));
            const float ei = ex2((mi - m) * LOG2E);
            float den = ei * lds_f(ma + 4);
            den += __shfl_xor_sync(0xffffffffu, den, 1);
            den += __shfl_xor_sync(0xffffffffu, den, 2);
            den += __shfl_xor_sync(0xffffffffu, den, 4);
            wv = ei * rcp(den);
        }
#pragma unroll 1
        for (int hh = 0; hh < n_heads; hh++) {
            float w[CL];
#pragma unroll
            for (int s = 0; s < CL; s++) w[s] = __shfl_sync(0xffffffffu, wv, hh * CL + s);
            uint32_t* dst = g_x + D_FF + head_at(cl, hh, tri) * D_HEAD + rank * 32 + lane;
            const uint32_t src = sb + SM_OP + hh * 1024 + lane * 4;
            mbar_wait(bar + BAR_O + hh * 8, 0);
            float v[CL];
#pragma unroll
            for (int s = 0; s < CL; s++) v[s] = lds_f(src + s * 128);
            const float o = (fmaf(w[1], v[1], w[0] * v[0]) + fmaf(w[3], v[3], w[2] * v[2])) +
                            (fmaf(w[5], v[5], w[4] * v[4]) + fmaf(w[7], v[7], w[6] * v[6]));
            ll_store(dst, __float_as_uint(bf16r(o)) | tag);
        }
        if (fin) {
            mbar_wait(bar + BAR_G, 0);
            const uint32_t g = pack_bf16(silu_f(bf16r(lds_colsum(sb + SM_FG + lane * 4))), 0.f);
            asm volatile("{\n.reg .pred p;\nsetp.eq.u32 p, %2, 0;\n@p st.relaxed.gpu.global.b32 [%0], %1;\n}" ::"l"(g_epoch), "r"(epoch + 1u), "r"(oc + rank + lane) : "memory");
            mbar_wait(bar + BAR_S, 0);
            uint32_t res = pack_bf16(lds_colsum(sb + SM_FS + lane * 4), 0.f);
            asm("mul.rn.bf16x2 %0, %0, %1;" : "+r"(res) : "r"(g));
            asm("add.rn.bf16x2 %0, %0, %1;" : "+r"(res) : "r"(xv));
            if (lane < 16) *out = (uint16_t)res;
        }
        return;
    }
    if (warp >= N_CONS_WARPS + 2) {
        const int gw = warp - (N_CONS_WARPS + 2);
        mbar_wait(bar + BAR_GO, 0);
#pragma unroll 1
        for (int round = 0; round < 2; round++) {
            const int i0 = round * 4 + 2 + gw;
            const uint32_t* src0 = g_x + tail_row(rank, i0) + lane * 4;
            const uint32_t* src1 = g_x + tail_row(rank, gw) + lane * 4;
            if (round == 1) {
                named_arrive(8, N_CONS + N_GATHER);
                mbar_wait(bar + BAR_GO + 8, 0);
                mbar_wait(bar_full + ((pos_t + GATE_LATE) & (N_SLOT - 1)) * 8, ((pos_t + GATE_LATE) >> 4) & 1);
            }
            uint4 v0 = make_uint4(0u, 0u, 0u, 0u), v1 = v0;
            const bool second = round == 0 && gw < 2 && lane < 24;
            uint32_t miss0 = lane < 24, miss1 = second;
            unsigned n = 0;
#pragma unroll 1
            while (true) {
                ll_ld4_if(v0, src0, miss0);
                ll_ld4_if(v1, src1, miss1);
                if (ll_bad4(v0, tag) == 0) miss0 = 0;
                if (ll_bad4(v1, tag) == 0) miss1 = 0;
                if (__all_sync(0xffffffffu, (miss0 | miss1) == 0) || ++n > SPIN_LIMIT) break;
            }
            if (lane < 24)
                *reinterpret_cast<uint2*>(sp + SM_OV + i0 * 192 + lane * 8) = make_uint2(__byte_perm(v0.x, v0.y, 0x7632), __byte_perm(v0.z, v0.w, 0x7632));
            if (second)
                *reinterpret_cast<uint2*>(sp + SM_OV + gw * 192 + lane * 8) = make_uint2(__byte_perm(v1.x, v1.y, 0x7632), __byte_perm(v1.z, v1.w, 0x7632));
        }
        named_arrive(3, N_CONS + N_GATHER);
        return;
    }


    const int q4 = lane & 3, g8 = lane >> 2;
    const int rowT = (lane & 7) + ((lane >> 4) << 3), hiT = (lane >> 3) & 1;
    const uint32_t off_v = ((3 * rowT + (warp >> 1)) * 128 + ((hiT ^ ((3 * rowT + (warp >> 1)) & 7)) << 4)) ^ ((warp & 1) << 6);

    if (warp < V_WARPS) {
#pragma unroll 1
        for (int part = 0; part <= tri; part++) {
            const uint32_t xa = sb + SM_XN + ((part ? rank * 16 - 1280 : (rank & 3) * 16) + 2 * q4) * 2, xs = 128 << part;
            float acc[2][4] = {};
#pragma unroll 1
            for (int p = part * 10; p < 10 + part * 5; p++) {
                const uint32_t b0 = lds32(xa + p * xs), b1 = lds32(xa + p * xs + 16);
                mbar_wait(bar_full + (p >> 1) * 8, 0);
                uint32_t a[4];
                ldsm_x4_t(a, sb + SM_RING + p * PIECE_BYTES + off_v);
                mma_bf16(acc[0], a, b0, b1);
                ldsm_x4_t(a, sb + SM_RING + p * PIECE_BYTES + (off_v ^ 32));
                mma_bf16(acc[1], a, b0, b1);
                __syncwarp();
                if (lane == 0) mbar_arrive_n(bar_empty + (p >> 1) * 8, p == 14 ? RELEASE / V_WARPS : RELEASE / V_WARPS / 2);
            }
            const float v = pick4(acc[0][0], acc[0][2], acc[1][0], acc[1][2], q4);
            const uint32_t dst = sb + SM_QP + ((part * CL + rank) * D_HEAD + warp * 32 + q4 * 8 + g8) * 4;
#pragma unroll
            for (int d = 0; d < CL; d++) st_async(mapa(dst, d), v, mapa(bar + BAR_Q, d));
        }
        mbar_wait(bar + BAR_Q, 0);
        const float* qp = reinterpret_cast<const float*>(sp + SM_QP) + tid;
        __nv_bfloat16* qs = reinterpret_cast<__nv_bfloat16*>(sp + SM_Q) + tid;
        qs[0] = __float2bfloat16_rn((qp[0] + qp[192]) + (qp[384] + qp[576]));
        qs[(tri + 1) * D_HEAD] = __float2bfloat16_rn((qp[768] + qp[960]) + (qp[1152] + qp[1344]));
        if (tri) {
            qp += CL * D_HEAD;
            qs[D_HEAD] = __float2bfloat16_rn(((qp[0] + qp[192]) + (qp[384] + qp[576])) + ((qp[768] + qp[960]) + (qp[1152] + qp[1344])));
        }
    }
    named_sync(1, N_CONS);

    {
        const int rowN = (lane & 7) + (((lane >> 3) & 1) << 3), hiN = lane >> 4;
#pragma unroll 1
        for (int hh = 0; hh < n_heads; hh++) {
            float s0 = 0.f, s1 = 0.f;
#pragma unroll 1
            for (int i = 0; i < 2; i++) {
                const int u = hh * HEAD_TILES + i * 8 + warp, pos = pos_k + u, slot = pos & (N_SLOT - 1);
                mbar_wait(bar_full + slot * 8, (pos >> 4) & 1);
                const uint32_t tb = sb + SM_RING + slot * TILE_BYTES;
                float acc[2][2][4] = {};
#pragma unroll 1
                for (int j = 0; j < 3; j++) {
                    const int swz = u < 2 ? 0 : (3 * rowN + j) & 7;
                    const uint32_t oj = tb + (3 * rowN + j) * 128 + ((hiN ^ swz) << 4);
                    const uint32_t qa = sb + SM_Q + (hh * D_HEAD + j * 64 + 2 * q4) * 2;
#pragma unroll
                    for (int k = 0; k < 4; k++) {
                        const uint32_t b0 = lds32(qa + k * 32), b1 = lds32(qa + k * 32 + 16);
                        uint32_t a[4];
                        ldsm_x4(a, oj ^ (k << 5));
                        mma_bf16(acc[0][k & 1], a, b0, b1);
                        ldsm_x4(a, (oj + PIECE_BYTES) ^ (k << 5));
                        mma_bf16(acc[1][k & 1], a, b0, b1);
                    }
                }
                __syncwarp();
                if (lane == 0) mbar_arrive_n(bar_empty + slot * 8, RELEASE);
                const float raw = pick4(acc[0][0][0] + acc[0][1][0], acc[0][0][2] + acc[0][1][2],
                                        acc[1][0][0] + acc[1][1][0], acc[1][0][2] + acc[1][1][2], q4);
                s0 = s1;
                s1 = bf16r(bf16r(raw) * 0.07216878364870323f);
            }
            float m = fmaxf(s0, s1);
#pragma unroll
            for (int o = 16; o > 0; o >>= 1) m = fmaxf(m, __shfl_xor_sync(0xffffffffu, m, o));
            if (lane == 0) sst[hh * 8 + warp] = m;
            named_sync(1, N_CONS);
#pragma unroll
            for (int w = 0; w < 8; w++) m = fmaxf(m, sst[hh * 8 + w]);
            const float p0 = ex2((s0 - m) * LOG2E), p1 = ex2((s1 - m) * LOG2E);
            float l = p0 + p1;
#pragma unroll
            for (int o = 16; o > 0; o >>= 1) l += __shfl_xor_sync(0xffffffffu, l, o);
            if (lane == 0) sst[24 + hh * 8 + warp] = l;
            __nv_bfloat16* ps = reinterpret_cast<__nv_bfloat16*>(sp + SM_P) + hh * 512 + warp * 32 + q4 * 8 + g8;
            ps[0] = __float2bfloat16_rn(p0);
            ps[256] = __float2bfloat16_rn(p1);
        }
        named_sync(1, N_CONS);
        if (warp == 7 && lane < n_heads * CL && (lane & 7) < V_WARPS) {
            const float* st = sst + (lane & 24);
            float m = st[0], l = st[24];
#pragma unroll
            for (int w = 1; w < 8; w++) { m = fmaxf(m, st[w]); l += st[24 + w]; }
            st_async2(mapa(sb + SM_ML + ((lane & 24) + rank) * 8, lane & 7), m, l, mapa(bar + BAR_ML, lane & 7));
        }
    }

    const uint32_t off_w = (warp >> 2) * PIECE_BYTES + rowT * 128 + (((((warp & 3) << 1) | hiT) ^ (rowT & 7)) << 4);

    if (ffn) {
#pragma unroll 1
        for (int res = 0; res < 2; res++) {
            float acc[3][4] = {};
#pragma unroll 1
            for (int i = 0; i < W_TILES / 2; i++) {
                const int pos = pos_w + res * (W_TILES / 2) + i, slot = pos & (N_SLOT - 1);
                const uint32_t xa = sb + SM_XN + (i * 96 + (warp >> 2) * 48 + 2 * q4) * 2;
                mbar_wait(bar_full + slot * 8, (pos >> 4) & 1);
#pragma unroll
                for (int k = 0; k < 3; k++) {
                    uint32_t a[4];
                    ldsm_x4_t(a, sb + SM_RING + slot * TILE_BYTES + off_w + k * 2048);
                    mma_bf16(acc[k], a, lds32(xa + k * 32), lds32(xa + k * 32 + 16));
                }
                __syncwarp();
                if (lane == 0) mbar_arrive_n(bar_empty + slot * 8, RELEASE / N_CONS_WARPS);
            }
            if (q4 < 2)
                reinterpret_cast<float*>(sp + SM_FG)[res * 128 + warp * 16 + q4 * 8 + g8] =
                    q4 ? (acc[0][2] + acc[1][2]) + acc[2][2] : (acc[0][0] + acc[1][0]) + acc[2][0];
        }
        named_sync(1, N_CONS);
        if (warp >= V_WARPS) {
            const float* f = reinterpret_cast<const float*>(sp + SM_FG) + (tid & 63);
            const float h = bf16r(bf16r(silu_f(bf16r(f[0] + f[64]))) * bf16r(f[128] + f[192]));
            ll_store(g_x + (cta - CL_FFN * CL) * 64 + (tid & 63), __float_as_uint(h) | tag);
        }
    }

    if (warp < V_WARPS) {
        const uint32_t rdst = mapa(sb + SM_OP + rank * 128 + (q4 * 8 + g8) * 4, warp), rbar = mapa(bar + BAR_O, warp);
#pragma unroll 1
        for (int hh = 0; hh < n_heads; hh++) {
            float oacc[2][2][4] = {};
#pragma unroll 2
            for (int u = hh * HEAD_TILES; u < (hh + 1) * HEAD_TILES; u++) {
                const int pos = pos_v + u, slot = pos & (N_SLOT - 1);
                uint32_t ta = sb + SM_RING + slot * TILE_BYTES + off_v, tc = ta ^ 32;
                asm volatile("" : "+r"(ta), "+r"(tc));
                const uint32_t pa = sb + SM_P + (u * 32 + 2 * q4) * 2;
                const uint32_t b0 = lds32(pa), b1 = lds32(pa + 16), b2 = lds32(pa + 32), b3 = lds32(pa + 48);
                mbar_wait(bar_full + slot * 8, (pos >> 4) & 1);
                uint32_t a[4][4];
                ldsm_x4_t(a[0], ta);
                ldsm_x4_t(a[1], tc);
                ldsm_x4_t(a[2], ta + PIECE_BYTES);
                ldsm_x4_t(a[3], tc + PIECE_BYTES);
                mma_bf16(oacc[0][0], a[0], b0, b1);
                mma_bf16(oacc[1][0], a[1], b0, b1);
                mma_bf16(oacc[0][1], a[2], b2, b3);
                mma_bf16(oacc[1][1], a[3], b2, b3);
                __syncwarp();
                if (lane == 0) mbar_arrive_n(bar_empty + slot * 8, RELEASE / V_WARPS);
            }
            const float v = pick4(oacc[0][0][0] + oacc[0][1][0], oacc[0][0][2] + oacc[0][1][2],
                                  oacc[1][0][0] + oacc[1][1][0], oacc[1][0][2] + oacc[1][1][2], q4);
            st_async(rdst + hh * 1024, v, rbar + hh * 8);
        }
    }
    if (!owner) return;

    {
        constexpr int P0 = POS_K2 + 4 * HEAD_TILES;
        const uint32_t rdst = mapa(sb + SM_FG + (rank * 2 + (warp >> 2)) * 64 + g8 * 8, warp & 3);
        const uint32_t rbar = mapa(bar + BAR_G, warp & 3);
        const uint32_t va = sb + SM_OV + ((warp >> 2) * 48 + 2 * q4) * 2, tw = sb + SM_RING + off_w;
        named_sync(8, N_CONS + N_GATHER);
        auto send = [&](const float (&acc)[3][4], uint32_t dst, uint32_t mb) {
            if (q4 == 0) st_async2(dst, (acc[0][0] + acc[1][0]) + acc[2][0], (acc[0][2] + acc[1][2]) + acc[2][2], mb);
        };
        float acc[3][4] = {};
#pragma unroll 1
        for (int i = 0; i < 6; i++) {
            const int slot = (P0 + i) & (N_SLOT - 1);
            uint32_t b[3][2];
#pragma unroll
            for (int k = 0; k < 3; k++) { b[k][0] = lds32(va + i * 192 + k * 32); b[k][1] = lds32(va + i * 192 + k * 32 + 16); }
            mbar_wait(bar_full + slot * 8, ((P0 + i) >> 4) & 1);
#pragma unroll
            for (int k = 0; k < 3; k++) {
                uint32_t a[4];
                ldsm_x4_t(a, tw + slot * TILE_BYTES + k * 2048);
                mma_bf16(acc[k], a, b[k][0], b[k][1]);
            }
            if (i == 1) {
                send(acc, rdst, rbar);
#pragma unroll
                for (int k = 0; k < 3; k++) acc[k][0] = acc[k][1] = acc[k][2] = acc[k][3] = 0.f;
            }
        }
        static_assert(((P0 + 6) >> 4) % 2 == 0 && (P0 + 9) >> 4 == (P0 + 6) >> 4, "both kinds of barrier complete a phase of parity 0");
        const uint32_t hb = warp < 4 ? bar_full + ((P0 + 6) & (N_SLOT - 1)) * 8 : bar + BAR_HALF;
        uint32_t a[4][3][4], b[4][3][2];
        named_sync(3, N_CONS + N_GATHER);
#pragma unroll
        for (int i = 0; i < 4; i++)
#pragma unroll
            for (int k = 0; k < 3; k++) { b[i][k][0] = lds32(va + (6 + i) * 192 + k * 32); b[i][k][1] = lds32(va + (6 + i) * 192 + k * 32 + 16); }
#pragma unroll
        for (int i = 0; i <= 4; i++) {
            if (i < 4) {
                const int slot = (P0 + 6 + i) & (N_SLOT - 1);
                mbar_wait(hb + i * 8, 0);
#pragma unroll
                for (int k = 0; k < 3; k++) ldsm_x4_t(a[i][k], tw + slot * TILE_BYTES + k * 2048);
            }
            if (i >= 1) {
#pragma unroll
                for (int k = 0; k < 3; k++) mma_bf16(acc[k], a[i - 1][k], b[i - 1][k][0], b[i - 1][k][1]);
            }
        }
        send(acc, rdst + (SM_FS - SM_FG), rbar + (BAR_S - BAR_G));
    }
}

typedef CUresult (*EncodeTiledFn)(CUtensorMap*, CUtensorMapDataType, cuuint32_t, void*, const cuuint64_t*,
                                  const cuuint64_t*, const cuuint32_t*, const cuuint32_t*, CUtensorMapInterleave,
                                  CUtensorMapSwizzle, CUtensorMapL2promotion, CUtensorMapFloatOOBfill);

void encode_map(EncodeTiledFn fn, CUtensorMap* m, const void* base, cuuint64_t rows, cuuint64_t cols, cuuint32_t b1, cuuint32_t b2) {
    const cuuint64_t dims[3] = {64, cols / 64, rows};
    const cuuint64_t strides[2] = {128, cols * 2};
    const cuuint32_t box[3] = {64, b1, b2};
    const cuuint32_t estr[3] = {1, 1, 1};
    fn(m, CU_TENSOR_MAP_DATA_TYPE_BFLOAT16, 3, const_cast<void*>(base), dims, strides, box, estr,
       CU_TENSOR_MAP_INTERLEAVE_NONE, CU_TENSOR_MAP_SWIZZLE_128B, CU_TENSOR_MAP_L2_PROMOTION_NONE,
       CU_TENSOR_MAP_FLOAT_OOB_FILL_NONE);
}

}

extern "C" void kernel_launch(void* const* d_in, const int* in_sizes, int n_in, void* d_out, int out_size) {
    (void)in_sizes; (void)n_in; (void)out_size;
    static EncodeTiledFn encode = nullptr;
    static double pace_scale = 1.0;
    static void* scratch = nullptr;
    if (!encode) {
        int dev = 0, mem_khz = 0, bus_bits = 0;
        cudaGetDevice(&dev);
        cudaDeviceGetAttribute(&mem_khz, cudaDevAttrMemoryClockRate, dev);
        cudaDeviceGetAttribute(&bus_bits, cudaDevAttrGlobalMemoryBusWidth, dev);
        const double peak_gbs = 2.0 * mem_khz * 1e-6 * bus_bits / 8.0;
        if (peak_gbs > 0.0) pace_scale = PACE_REF_GBS / peak_gbs;
        void* fn = nullptr;
        cudaDriverEntryPointQueryResult qr;
        cudaGetDriverEntryPoint("cuTensorMapEncodeTiled", &fn, cudaEnableDefault, &qr);
        encode = reinterpret_cast<EncodeTiledFn>(fn);
        cudaFuncSetAttribute(fused_decode_kernel, cudaFuncAttributeMaxDynamicSharedMemorySize, SM_ALLOC);
        cudaGetSymbolAddress(&scratch, g_scratch);
    }
    CUtensorMap tm_k, tm_v, tm_wq, tm_w1, tm_w3, tm_wo, tm_w2;
    encode_map(encode, &tm_k, d_in[1], (cuuint64_t)N_HEAD * SEQ, D_HEAD, 3, 32);
    encode_map(encode, &tm_v, d_in[2], (cuuint64_t)N_HEAD * SEQ, D_HEAD, 3, 32);
    encode_map(encode, &tm_wq, d_in[3], D_MODEL, N_HEAD * D_HEAD, 3, 16);
    encode_map(encode, &tm_w1, d_in[6], D_MODEL, D_FF, 1, 96);
    encode_map(encode, &tm_w3, d_in[7], D_MODEL, D_FF, 1, 96);
    encode_map(encode, &tm_wo, d_in[4], N_HEAD * D_HEAD, D_MODEL, 1, 48);
    encode_map(encode, &tm_w2, d_in[8], D_FF, D_MODEL, 1, 48);
    Params prm;
    prm.x = static_cast<const __nv_bfloat16*>(d_in[0]);
    prm.out = static_cast<__nv_bfloat16*>(d_out);
    prm.k = static_cast<const __nv_bfloat16*>(d_in[1]) + (size_t)(SEQ - WIN) * D_HEAD;
    prm.scratch = static_cast<uint32_t*>(scratch);
    auto step = [&](double pace, double bytes, int pieces) { return (uint16_t)(8.0 * pace * pace_scale * bytes / (128.0 * TILE_BYTES) / pieces); };
    const double b_wq = 2.0 * D_MODEL * N_HEAD * D_HEAD;
    const double b_mid = 4.0 * N_HEAD * WIN * D_HEAD - 2.0 * N_CTA * TILE_BYTES + 4.0 * D_MODEL * D_FF;
    const double b_tail = 2.0 * D_MODEL * (D_FF + N_HEAD * D_HEAD);
    prm.step_wq2 = step(PACE_HEAD, b_wq, 10);
    prm.step_wq3 = step(PACE_HEAD, b_wq, 15);
    prm.step_own = step(PACE_MID, b_mid, 4 * HEAD_TILES - 2);
    prm.step_ffn = step(PACE_MID, b_mid, 4 * HEAD_TILES - 2 + W_TILES);
    prm.step_tri = step(PACE_MID, b_mid, 6 * HEAD_TILES - 2);
    prm.step_tail = step(PACE_TAIL, b_tail, TAIL_TILES);
    prm.late = (uint16_t)(4096.0 * PACE_LATE / PACE_MID + 0.5);
    prm.pad = 0;
    fused_decode_kernel<<<N_CTA, N_THREADS, SM_ALLOC, cudaStreamPerThread>>>(prm, tm_wq, tm_w1, tm_w3, tm_k, tm_v, tm_wo, tm_w2);
}
```

```cpp
#include <cuda_runtime.h>
#include <cuda_bf16.h>
#include <cuda.h>
#include <stdint.h>

namespace {

constexpr int D_MODEL = 640;
constexpr int N_HEAD = 32;
constexpr int D_HEAD = 192;
constexpr int SEQ = 32768;
constexpr int WIN = 4096;
constexpr int D_FF = 1536;

constexpr int CL = 8;
constexpr int N_CL = 15;
constexpr int N_CTA = CL * N_CL;
constexpr int CL_FFN = 1, CL_TRI = CL_FFN + 3, CL_OWN = CL_TRI + 2;
constexpr int TILE_BYTES = 12288;
constexpr int PIECE_BYTES = TILE_BYTES / 2;
constexpr int N_SLOT = 16;
constexpr int HEAD_TILES = WIN / CL / 32;
constexpr int W_TILES = 14;
constexpr int TAIL_TILES = 10;
constexpr int POS_K2 = 5, POS_K3 = 8;

constexpr int N_CONS_WARPS = 8;
constexpr int N_CONS = N_CONS_WARPS * 32;
constexpr int N_GATHER = 128;
constexpr int N_THREADS = N_CONS + 64 + N_GATHER;
constexpr int V_WARPS = 6;
constexpr int RELEASE = 24;

constexpr double PACE_HEAD = 490, PACE_MID = 479, PACE_LATE = 495, PACE_TAIL = 482, PACE_REF_GBS = 3352.32;
constexpr int START_DELAY = 140;
constexpr int WINDOW_OWN = 5, WINDOW_FFN = 6, WINDOW_FAST = 8;
constexpr int SLIP = 50;
constexpr int GATE_EARLY = 4;
constexpr int GATE_LATE = 3;

constexpr unsigned SPIN_LIMIT = 1u << 22;

constexpr int SM_RING = 0;
constexpr int SM_BAR = N_SLOT * TILE_BYTES;
constexpr int BAR_FULL = 0, BAR_EMPTY = 128, BAR_GO = 256, BAR_Q = 272, BAR_ML = 280, BAR_O = 288, BAR_G = 312, BAR_S = 320, BAR_X = 328,
              BAR_HALF = 336, BAR_READY = 368;
constexpr int SM_T0 = SM_BAR + 448, SM_EPOCH = SM_BAR + 452;
constexpr int SM_XN = SM_BAR + 512;
constexpr int SM_Q = SM_XN + 1408;
constexpr int SM_ST = SM_Q + 1152;
constexpr int SM_ML = SM_ST + 256;
constexpr int SM_P = SM_ML + 256;
constexpr int SM_QP = SM_P + 3072;
constexpr int SM_OP = SM_QP + 12288;
constexpr int SM_OV = SM_OP + 3072;
constexpr int SM_FG = SM_OV + 1920;
constexpr int SM_FS = SM_FG + 1024;
constexpr int SM_ALLOC = SM_FS + 1024 + 1024;

constexpr int XO_H = 32;
constexpr int XO_END = XO_H + D_FF + N_HEAD * D_HEAD;
__device__ __align__(128) uint32_t g_scratch[XO_END];

__device__ __forceinline__ uint32_t smem_u32(const void* p) { return (uint32_t)__cvta_generic_to_shared(p); }

__device__ __forceinline__ void mbar_init(uint32_t bar, uint32_t cnt) {
    asm volatile("mbarrier.init.shared::cta.b64 [%0], %1;" ::"r"(bar), "r"(cnt) : "memory");
}
__device__ __forceinline__ void mbar_expect_tx(uint32_t bar, uint32_t bytes) {
    asm volatile("mbarrier.arrive.expect_tx.shared::cta.b64 _, [%0], %1;" ::"r"(bar), "r"(bytes) : "memory");
}
__device__ __forceinline__ void mbar_arrive(uint32_t bar) {
    asm volatile("mbarrier.arrive.shared::cta.b64 _, [%0];" ::"r"(bar) : "memory");
}
__device__ __forceinline__ void mbar_wait(uint32_t bar, uint32_t parity) {
    asm volatile(
        "{\n.reg .pred p, q;\n.reg .u32 n;\n"
        "mov.u32 n, 0;\n"
        "WAIT_LOOP:\n"
        "add.u32 n, n, 1;\n"
        "setp.lt.u32 q, n, %2;\n"
        "mbarrier.try_wait.parity.shared::cta.b64 p, [%0], %1;\n"
        "and.pred q, q, !p;\n"
        "@q bra WAIT_LOOP;\n}"
        ::"r"(bar), "r"(parity), "n"(SPIN_LIMIT) : "memory");
}
__device__ __forceinline__ void named_sync(int id, int n) {
    asm volatile("bar.sync %0, %1;" ::"r"(id), "r"(n) : "memory");
}
__device__ __forceinline__ void named_arrive(int id, int n) {
    asm volatile("bar.arrive %0, %1;" ::"r"(id), "r"(n) : "memory");
}
__device__ __forceinline__ uint64_t stream_policy() {
    uint64_t pol;
    asm volatile("createpolicy.fractional.L2::evict_first.b64 %0, 1.0;" : "=l"(pol));
    return pol;
}
__device__ __forceinline__ void bulk_load(uint32_t dst, const void* src, uint32_t bytes, uint32_t bar, uint64_t pol) {
    asm volatile("cp.async.bulk.shared::cluster.global.mbarrier::complete_tx::bytes.L2::cache_hint [%0], [%1], %2, [%3], %4;"
                 ::"r"(dst), "l"(src), "r"(bytes), "r"(bar), "l"(pol) : "memory");
}
__device__ __forceinline__ void tma_3d(uint32_t dst, const CUtensorMap* tm, int c0, int c1, int c2, uint32_t bar, uint64_t pol) {
    asm volatile("cp.async.bulk.tensor.3d.shared::cluster.global.mbarrier::complete_tx::bytes.L2::cache_hint [%0], [%1, {%3, %4, %5}], [%2], %6;"
                 ::"r"(dst), "l"(tm), "r"(bar), "r"(c0), "r"(c1), "r"(c2), "l"(pol) : "memory");
}
__device__ __forceinline__ void prefetch_tmap(const CUtensorMap* tm) {
    asm volatile("prefetch.tensormap [%0];" ::"l"(tm) : "memory");
}
__device__ __forceinline__ void ldsm_x4(uint32_t (&r)[4], uint32_t addr) {
    asm volatile("ldmatrix.sync.aligned.m8n8.x4.shared.b16 {%0,%1,%2,%3}, [%4];"
                 : "=r"(r[0]), "=r"(r[1]), "=r"(r[2]), "=r"(r[3]) : "r"(addr) : "memory");
}
__device__ __forceinline__ void ldsm_x4_t(uint32_t (&r)[4], uint32_t addr) {
    asm volatile("ldmatrix.sync.aligned.m8n8.x4.trans.shared.b16 {%0,%1,%2,%3}, [%4];"
                 : "=r"(r[0]), "=r"(r[1]), "=r"(r[2]), "=r"(r[3]) : "r"(addr) : "memory");
}
__device__ __forceinline__ void mma_bf16(float (&c)[4], const uint32_t (&a)[4], uint32_t b0, uint32_t b1) {
    asm volatile("mma.sync.aligned.m16n8k16.row.col.f32.bf16.bf16.f32 {%0,%1,%2,%3}, {%4,%5,%6,%7}, {%8,%9}, {%0,%1,%2,%3};"
                 : "+f"(c[0]), "+f"(c[1]), "+f"(c[2]), "+f"(c[3])
                 : "r"(a[0]), "r"(a[1]), "r"(a[2]), "r"(a[3]), "r"(b0), "r"(b1));
}
__device__ __forceinline__ float bf16r(float v) {
    uint32_t p;
    asm("cvt.rn.bf16x2.f32 %0, %1, %2;" : "=r"(p) : "f"(v), "f"(0.f));
    return __uint_as_float(p);
}
__device__ __forceinline__ uint32_t lds32(uint32_t addr) {
    uint32_t v;
    asm volatile("ld.shared.b32 %0, [%1];" : "=r"(v) : "r"(addr) : "memory");
    return v;
}
__device__ __forceinline__ float bf_lo(uint32_t v) { return __uint_as_float(v << 16); }
__device__ __forceinline__ float bf_hi(uint32_t v) { return __uint_as_float(v & 0xffff0000u); }
__device__ __forceinline__ uint32_t pack_bf16(float lo, float hi) {
    const __nv_bfloat162 p = __floats2bfloat162_rn(lo, hi);
    return *reinterpret_cast<const uint32_t*>(&p);
}
__device__ __forceinline__ uint32_t now_ns() {
    unsigned long long t;
    asm volatile("mov.u64 %0, %%globaltimer;" : "=l"(t));
    return (uint32_t)t;
}

__device__ __forceinline__ void wait_until(uint32_t t_start, uint32_t deadline) {
    unsigned n = 0;
    while (now_ns() - t_start < deadline && ++n < SPIN_LIMIT) {}
}

__device__ __forceinline__ uint32_t ll_bad4(const uint4& v, uint32_t tag) {
    uint32_t lo, hi;
    asm("lop3.b32 %0, %1, %2, %3, 0x7E;" : "=r"(lo) : "r"(v.x), "r"(v.y), "r"(tag));
    asm("lop3.b32 %0, %1, %2, %3, 0x7E;" : "=r"(hi) : "r"(v.z), "r"(v.w), "r"(tag));
    return (lo | hi) & 3u;
}
__device__ __forceinline__ float ex2(float v) {
    float r;
    asm("ex2.approx.ftz.f32 %0, %1;" : "=f"(r) : "f"(v));
    return r;
}
__device__ __forceinline__ float rcp(float v) {
    float r;
    asm("rcp.approx.ftz.f32 %0, %1;" : "=f"(r) : "f"(v));
    return r;
}
constexpr float LOG2E = 1.4426950408889634f;
__device__ __forceinline__ void ll_store(uint32_t* p, uint32_t w) {
    asm volatile("st.relaxed.gpu.global.b32 [%0], %1;" ::"l"(p), "r"(w) : "memory");
}
__device__ __forceinline__ uint32_t ll_ld(const uint32_t* p) {
    uint32_t v;
    asm volatile("ld.relaxed.gpu.global.b32 %0, [%1];" : "=r"(v) : "l"(p) : "memory");
    return v;
}
__device__ __forceinline__ float pick4(float a, float b, float c, float d, int j) {
    const float lo = (j & 1) ? b : a, hi = (j & 1) ? d : c;
    return (j & 2) ? hi : lo;
}
__device__ __forceinline__ float silu_f(float v) { return v * rcp(1.f + ex2(-LOG2E * v)); }

__device__ __forceinline__ void mbar_arrive_n(uint32_t bar, uint32_t n) {
    asm volatile("mbarrier.arrive.shared::cta.b64 _, [%0], %1;" ::"r"(bar), "r"(n) : "memory");
}
__device__ __forceinline__ uint32_t mapa(uint32_t addr, uint32_t rank) {
    uint32_t d;
    asm("mapa.shared::cluster.u32 %0, %1, %2;" : "=r"(d) : "r"(addr), "r"(rank));
    return d;
}
__device__ __forceinline__ void st_async(uint32_t dst, float v, uint32_t bar) {
    asm volatile("st.async.weak.shared::cluster.mbarrier::complete_tx::bytes.f32 [%0], %1, [%2];" ::"r"(dst), "f"(v), "r"(bar) : "memory");
}
__device__ __forceinline__ void st_async2(uint32_t dst, float a, float b, uint32_t bar) {
    asm volatile("st.async.weak.shared::cluster.mbarrier::complete_tx::bytes.v2.f32 [%0], {%1, %2}, [%3];" ::"r"(dst), "f"(a), "f"(b), "r"(bar) : "memory");
}
__device__ __forceinline__ void cluster_arrive() { asm volatile("barrier.cluster.arrive.relaxed.aligned;" ::: "memory"); }
__device__ __forceinline__ void cluster_wait() { asm volatile("barrier.cluster.wait.aligned;" ::: "memory"); }
__device__ __forceinline__ void ll_ld4_if(uint4& v, const uint32_t* p, uint32_t cond) {
    asm volatile("{\n.reg .pred p;\nsetp.ne.u32 p, %5, 0;\n@p ld.relaxed.gpu.global.v4.b32 {%0,%1,%2,%3}, [%4];\n}"
                 : "+r"(v.x), "+r"(v.y), "+r"(v.z), "+r"(v.w) : "l"(p), "r"(cond) : "memory");
}
__device__ __forceinline__ float lds_f(uint32_t addr) { return __uint_as_float(lds32(addr)); }
__device__ __forceinline__ float lds_colsum(uint32_t base, int lane) {
    const uint32_t addr = base + ((lane >> 3) ^ ((lane >> 2) & 1)) * 64 + (lane & 3) * 16;
    uint32_t v[4][4];
#pragma unroll
    for (int i = 0; i < 4; i++) ldsm_x4(v[i], addr + i * 256);
    float t[4];
#pragma unroll
    for (int i = 0; i < 4; i++)
        t[i] = (__uint_as_float(v[i][0]) + __uint_as_float(v[i][1])) + (__uint_as_float(v[i][2]) + __uint_as_float(v[i][3]));
    return ((t[0] + t[1]) + t[2]) + t[3];
}

constexpr uint32_t FIRST_MUL = 257, FIRST_MASK = 0x7807;
__device__ __forceinline__ int pair_head(int cl, int j) { return 2 * cl + j; }
__device__ __forceinline__ int third_head(int cl) { return 2 * N_CL + cl - CL_TRI; }
__device__ __forceinline__ int head_at(int cl, int hh, int tri) { return (hh & tri) ? third_head(cl) : pair_head(cl, hh >> tri); }
__device__ __forceinline__ int tail_row(int rank, int i) {
    if (i < 2) return i * 768 + rank * 96;
    const int j = 4 * (i - 2) + (rank >> 1), q = rank & 1;
    return D_FF + (2 * (j & 15) + (j >> 4)) * D_HEAD + q * 96;
}

struct Params {
    const __nv_bfloat16* x;
    __nv_bfloat16* out;
    const __nv_bfloat16* k;
    uint32_t* scratch;
    uint16_t step_wq2, step_wq3, step_own, step_ffn, step_tri, step_tail, late, pad;
};
static_assert(sizeof(Params) == 48, "Params must fill the rest of the first parameter line");

__global__ void __cluster_dims__(CL, 1, 1) __launch_bounds__(N_THREADS, 1)
fused_decode_kernel(const Params prm, const __grid_constant__ CUtensorMap tm_wq, const __grid_constant__ CUtensorMap tm_w1,
                    const __grid_constant__ CUtensorMap tm_w3, const __grid_constant__ CUtensorMap tm_k,
                    const __grid_constant__ CUtensorMap tm_v, const __grid_constant__ CUtensorMap tm_wo,
                    const __grid_constant__ CUtensorMap tm_w2) {
    extern __shared__ uint8_t smem_raw[];
    asm volatile("{\n.reg .pred p;\nsetp.lt.u32 p, %1, %2;\n@p prefetch.global.L2 [%0];\n}"
                 ::"l"(reinterpret_cast<const char*>(prm.k) + (size_t)(((blockIdx.x * FIRST_MUL) & FIRST_MASK) * (TILE_BYTES / 32) + threadIdx.x) * 32),
                   "r"(threadIdx.x), "n"(TILE_BYTES / 32) : "memory");
    const uint32_t sb = (smem_u32(smem_raw) + 1023u) & ~1023u;
    uint8_t* sp = smem_raw + (sb - smem_u32(smem_raw));
    const uint32_t bar = sb + SM_BAR;
    const uint32_t bar_full = bar + BAR_FULL, bar_empty = bar + BAR_EMPTY;

    const int tid = threadIdx.x;
    const int cta = blockIdx.x, cl = blockIdx.x / CL, rank = blockIdx.x % CL;
    const int tri = cl >= CL_TRI && cl < CL_OWN;
    const int pos_k = tri ? POS_K3 : POS_K2;
    volatile uint32_t* t_first = reinterpret_cast<volatile uint32_t*>(sp + SM_T0);
    if (tid == N_CONS) {
        const __nv_bfloat16* k0 = prm.k + (uint32_t)(pair_head(cl, 0) * SEQ + rank * 32) * (size_t)D_HEAD;
#pragma unroll
        for (int u = 1; u >= 0; u--) {
            const uint32_t fb = bar_full + (pos_k + u) * 8;
            mbar_init(fb, 1);
            asm volatile("fence.mbarrier_init.release.cluster;" ::: "memory");
            mbar_expect_tx(fb, TILE_BYTES);
            bulk_load(sb + SM_RING + (pos_k + u) * TILE_BYTES, k0 + u * (CL * 32 * D_HEAD), TILE_BYTES, fb, stream_policy());
            if (u == 1) *t_first = now_ns();
        }
    }
    if (tid == N_CONS + 32) prefetch_tmap(&tm_wq);
    const int warp = __shfl_sync(0xffffffffu, tid >> 5, 0), lane = tid & 31;
    const bool owner = cl < CL_FFN || cl >= CL_OWN, ffn = !owner && !tri;
    const int oc = cl < CL_FFN ? cl : cl - (CL_OWN - CL_FFN);
    const int n_heads = 2 + tri;
    const int pos_w = pos_k + n_heads * HEAD_TILES;
    const int pos_v = pos_w + (ffn ? W_TILES : 0);
    const int pos_t = pos_v + n_heads * HEAD_TILES;
    uint32_t* const g_epoch = prm.scratch;
    uint32_t* const g_x = prm.scratch + XO_H;
    const int n_start = owner ? N_THREADS : N_THREADS - 96;

    if (warp == N_CONS_WARPS) {
        if (lane == 0) {
#pragma unroll
            for (int i = 2; i < N_SLOT; i++) mbar_init(bar_full + ((pos_k + i) & (N_SLOT - 1)) * 8, 1);
            mbar_init(bar + BAR_READY, 1);
            asm volatile("fence.mbarrier_init.release.cluster;" ::: "memory");
        }
        __syncwarp();
        named_arrive(6, n_start);
        cluster_arrive();
        if (lane == 0) {
            const uint64_t pol = stream_policy();
            const uint32_t t_start = *t_first;
            uint32_t deadline = START_DELAY * 8;
            {
                const uint32_t step = tri ? prm.step_wq3 : prm.step_wq2;
#pragma unroll 1
                for (int p = 0; p < 10 + 5 * tri; p++) {
                    const uint32_t fb = bar_full + (p >> 1) * 8;
                    if (!(p & 1)) mbar_expect_tx(fb, p == 14 ? PIECE_BYTES : TILE_BYTES);
                    const int h = p < 10 ? pair_head(cl, rank >> 2) : third_head(cl);
                    const int row = p < 10 ? p * 64 + (rank & 3) * 16 : (p - 10) * 128 + rank * 16;
                    wait_until(t_start, deadline >> 3);
                    tma_3d(sb + SM_RING + p * PIECE_BYTES, &tm_wq, 0, h * 3, row, fb, pol);
                    deadline += step;
                }
            }
            mbar_wait(bar + BAR_READY, 0);
            uint32_t step = owner ? prm.step_own : (tri ? prm.step_tri : prm.step_ffn);
            int window = owner ? WINDOW_OWN : (tri ? WINDOW_FAST : WINDOW_FFN);
            const int pos_end = pos_t + (owner ? TAIL_TILES : 0);
            const int pos_late = pos_t - (owner ? 16 : (tri ? 24 : 20));
#pragma unroll 1
            for (int pos = pos_k + 2; pos < pos_end; pos++) {
                const int slot = pos & (N_SLOT - 1);
                const CUtensorMap* tm;
                int c1 = 0, row;
                if (pos >= pos_t) {
                    step = prm.step_tail;
                    window = WINDOW_FAST;
                    row = tail_row(rank, pos - pos_t);
                    tm = row < D_FF ? &tm_w2 : &tm_wo;
                    if (row >= D_FF) row -= D_FF;
                    c1 = oc;
                } else if (pos >= pos_w && pos < pos_v) {
                    const bool up = pos >= pos_w + W_TILES / 2;
                    tm = up ? &tm_w3 : &tm_w1;
                    c1 = cta - CL_FFN * CL;
                    row = (pos - pos_w - (up ? W_TILES / 2 : 0)) * 96;
                } else {
                    const int u = pos - (pos < pos_w ? pos_k : pos_v), hh = u >> 4;
                    tm = pos < pos_w ? &tm_k : &tm_v;
                    row = head_at(cl, hh, tri) * SEQ + (SEQ - WIN) + rank * 32 + (u & 15) * (CL * 32);
                }
                if (pos >= N_SLOT) mbar_wait(bar_empty + slot * 8, ((pos >> 4) - 1) & 1);
                if (pos >= pos_k + 2 + window) mbar_wait(bar_full + ((pos - window) & (N_SLOT - 1)) * 8, ((pos - window) >> 4) & 1);
                deadline = max(deadline, (now_ns() - t_start - SLIP) << 3);
                mbar_expect_tx(bar_full + slot * 8, pos >= pos_t + 6 ? PIECE_BYTES : TILE_BYTES);
                wait_until(t_start, deadline >> 3);
                tma_3d(sb + SM_RING + slot * TILE_BYTES, tm, 0, c1, row, bar_full + slot * 8, pol);
                if (pos >= pos_t)
                    tma_3d(sb + SM_RING + slot * TILE_BYTES + PIECE_BYTES, tm, 0, c1, row + 48,
                           pos >= pos_t + 6 ? bar + BAR_HALF + (pos - pos_t - 6) * 8 : bar_full + slot * 8, pol);
                deadline += step;
                if (pos == pos_late) step = step * prm.late >> 12;
                if (pos == pos_t - GATE_EARLY) mbar_arrive(bar + BAR_GO);
                if (pos == pos_t + GATE_LATE) mbar_arrive(bar + BAR_GO + 8);
            }
        }
        return;
    }

    if (warp > N_CONS_WARPS + 2 && !owner) return;
    if (tid == N_CONS + 32) {
#pragma unroll
        for (int i = 0; i < N_SLOT; i++) mbar_init(bar_empty + i * 8, RELEASE);
        asm volatile("fence.mbarrier_init.release.cluster;" ::: "memory");
    }
    if (tid == N_CONS + 64) {
#pragma unroll
        for (int i = BAR_GO; i < BAR_READY; i += 8) mbar_init(bar + i, 1);
#pragma unroll
        for (int i = BAR_HALF; i < BAR_READY; i += 8) mbar_expect_tx(bar + i, PIECE_BYTES);
        mbar_expect_tx(bar + BAR_X, D_MODEL * 2 + 4);
        mbar_expect_tx(bar + BAR_Q, (1 + tri) * CL * D_HEAD * 4);
        mbar_expect_tx(bar + BAR_ML, n_heads * CL * 8);
#pragma unroll
        for (int i = BAR_O; i <= BAR_S; i += 8) mbar_expect_tx(bar + i, 1024);
        asm volatile("fence.mbarrier_init.release.cluster;" ::: "memory");
    }
    __syncwarp();
    cluster_arrive();
    float* sst = reinterpret_cast<float*>(sp + SM_ST);
    if (tid < 8) *reinterpret_cast<uint2*>(sp + SM_XN + D_MODEL * 2 + tid * 8) = make_uint2(0u, 0u);
    if (rank == CL - 1 && warp >= V_WARPS && warp < N_CONS_WARPS) {
        if (warp == V_WARPS) {
            const uint32_t ep = ll_ld(g_epoch);
            cluster_wait();
            if (lane < CL) st_async(mapa(sb + SM_EPOCH, lane), __uint_as_float(ep), mapa(bar + BAR_X, lane));
        } else {
            uint2 u[5];
#pragma unroll
            for (int i = 0; i < 5; i++) u[i] = *reinterpret_cast<const uint2*>(prm.x + i * 128 + lane * 4);
            float s = 0.f;
#pragma unroll
            for (int i = 0; i < 5; i++) s += (bf_lo(u[i].x) + bf_hi(u[i].x)) + (bf_lo(u[i].y) + bf_hi(u[i].y));
#pragma unroll
            for (int o = 16; o > 0; o >>= 1) s += __shfl_xor_sync(0xffffffffu, s, o);
            const float mean = s * (1.f / D_MODEL);
            s = 0.f;
#pragma unroll
            for (int i = 0; i < 5; i++) {
                const float a = bf_lo(u[i].x) - mean, b = bf_hi(u[i].x) - mean, c = bf_lo(u[i].y) - mean, d = bf_hi(u[i].y) - mean;
                s += fmaf(a, a, b * b) + fmaf(c, c, d * d);
            }
#pragma unroll
            for (int o = 16; o > 0; o >>= 1) s += __shfl_xor_sync(0xffffffffu, s, o);
            const float mean_b = bf16r(mean);
            float den;
            asm("sqrt.approx.f32 %0, %1;" : "=f"(den) : "f"(bf16r(bf16r(s * (1.f / D_MODEL)) + 1e-5f)));
            const float inv = rcp(bf16r(den));
#pragma unroll
            for (int i = 0; i < 5; i++) {
                const uint32_t d0 = pack_bf16(bf_lo(u[i].x) - mean_b, bf_hi(u[i].x) - mean_b);
                const uint32_t d1 = pack_bf16(bf_lo(u[i].y) - mean_b, bf_hi(u[i].y) - mean_b);
                u[i] = make_uint2(pack_bf16(bf_lo(d0) * inv, bf_hi(d0) * inv), pack_bf16(bf_lo(d1) * inv, bf_hi(d1) * inv));
            }
            cluster_wait();
#pragma unroll 1
            for (int d = 0; d < CL; d++) {
                const uint32_t dst = mapa(sb + SM_XN + lane * 8, d), mb = mapa(bar + BAR_X, d);
#pragma unroll
                for (int i = 0; i < 5; i++) st_async2(dst + i * 256, __uint_as_float(u[i].x), __uint_as_float(u[i].y), mb);
            }
        }
        __syncwarp();
    }
    if (warp == N_CONS_WARPS + 1 && rank < V_WARPS) {
        ll_store(g_x + D_FF + pair_head(cl, 1) * D_HEAD + rank * 32 + lane, 0u);
    } else if (warp > N_CONS_WARPS && (!owner || warp == N_CONS_WARPS + 1)) {
        named_arrive(6, n_start);
        return;
    }
    named_sync(6, n_start);
    if (tid == 0) mbar_arrive(bar + BAR_READY);
    mbar_wait(bar + BAR_X, 0);
    const uint32_t epoch = lds32(sb + SM_EPOCH);
    const uint32_t tag = 1u + (epoch & 1u);

    if (warp == N_CONS_WARPS + 1) {
        const bool fin = owner && rank < 4;
        const int col = oc * 64 + rank * 16 + (lane & 1) * 8 + ((lane >> 1) & 7);
        uint16_t* const out = reinterpret_cast<uint16_t*>(prm.out) + col;
        mbar_wait(bar + BAR_ML, 0);
        uint32_t xv = 0;
        if (fin) xv = reinterpret_cast<const uint16_t*>(prm.x)[col];
        float wv;
        {
            const uint32_t ma = sb + SM_ML + (lane < n_heads * CL ? lane : 0) * 8;
            const float mi = lds_f(ma);
            float m = fmaxf(mi, __shfl_xor_sync(0xffffffffu, mi, 1));
            m = fmaxf(m, __shfl_xor_sync(0xffffffffu, m, 2));
            m = fmaxf(m, __shfl_xor_sync(0xffffffffu, m, 4));
            const float ei = ex2((mi - m) * LOG2E);
            float den = ei * lds_f(ma + 4);
            den += __shfl_xor_sync(0xffffffffu, den, 1);
            den += __shfl_xor_sync(0xffffffffu, den, 2);
            den += __shfl_xor_sync(0xffffffffu, den, 4);
            wv = ei * rcp(den);
        }
#pragma unroll 1
        for (int hh = 0; hh < n_heads; hh++) {
            float w[CL];
#pragma unroll
            for (int s = 0; s < CL; s++) w[s] = __shfl_sync(0xffffffffu, wv, hh * CL + s);
            uint32_t* dst = g_x + D_FF + head_at(cl, hh, tri) * D_HEAD + rank * 32 + lane;
            const uint32_t src = sb + SM_OP + hh * 1024 + lane * 4;
            mbar_wait(bar + BAR_O + hh * 8, 0);
            float v[CL];
#pragma unroll
            for (int s = 0; s < CL; s++) v[s] = lds_f(src + s * 128);
            const float o = (fmaf(w[1], v[1], w[0] * v[0]) + fmaf(w[3], v[3], w[2] * v[2])) +
                            (fmaf(w[5], v[5], w[4] * v[4]) + fmaf(w[7], v[7], w[6] * v[6]));
            ll_store(dst, __float_as_uint(bf16r(o)) | tag);
        }
        if (fin) {
            mbar_wait(bar + BAR_G, 0);
            const uint32_t g = pack_bf16(silu_f(bf16r(lds_colsum(sb + SM_FG, lane))), 0.f);
            asm volatile("{\n.reg .pred p;\nsetp.eq.u32 p, %2, 0;\n@p st.relaxed.gpu.global.b32 [%0], %1;\n}" ::"l"(g_epoch), "r"(epoch + 1u), "r"(oc + rank + lane) : "memory");
            mbar_wait(bar + BAR_S, 0);
            uint32_t res = pack_bf16(lds_colsum(sb + SM_FS, lane), 0.f);
            asm("mul.rn.bf16x2 %0, %0, %1;" : "+r"(res) : "r"(g));
            asm("add.rn.bf16x2 %0, %0, %1;" : "+r"(res) : "r"(xv));
            if (lane < 16) *out = (uint16_t)res;
        }
        return;
    }
    if (warp >= N_CONS_WARPS + 2) {
        const int gw = warp - (N_CONS_WARPS + 2);
        mbar_wait(bar + BAR_GO, 0);
#pragma unroll 1
        for (int round = 0; round < 2; round++) {
            const int i0 = round * 4 + 2 + gw;
            const uint32_t* src0 = g_x + tail_row(rank, i0) + lane * 4;
            const uint32_t* src1 = g_x + tail_row(rank, gw) + lane * 4;
            if (round == 1) {
                named_arrive(8, N_CONS + N_GATHER);
                mbar_wait(bar + BAR_GO + 8, 0);
                mbar_wait(bar_full + ((pos_t + GATE_LATE) & (N_SLOT - 1)) * 8, ((pos_t + GATE_LATE) >> 4) & 1);
            }
            uint4 v0 = make_uint4(0u, 0u, 0u, 0u), v1 = v0;
            const bool second = round == 0 && gw < 2 && lane < 24;
            uint32_t miss0 = lane < 24, miss1 = second;
            unsigned n = 0;
#pragma unroll 1
            while (true) {
                ll_ld4_if(v0, src0, miss0);
                ll_ld4_if(v1, src1, miss1);
                if (ll_bad4(v0, tag) == 0) miss0 = 0;
                if (ll_bad4(v1, tag) == 0) miss1 = 0;
                if (__all_sync(0xffffffffu, (miss0 | miss1) == 0) || ++n > SPIN_LIMIT) break;
            }
            if (lane < 24)
                *reinterpret_cast<uint2*>(sp + SM_OV + i0 * 192 + lane * 8) = make_uint2(__byte_perm(v0.x, v0.y, 0x7632), __byte_perm(v0.z, v0.w, 0x7632));
            if (second)
                *reinterpret_cast<uint2*>(sp + SM_OV + gw * 192 + lane * 8) = make_uint2(__byte_perm(v1.x, v1.y, 0x7632), __byte_perm(v1.z, v1.w, 0x7632));
        }
        named_arrive(3, N_CONS + N_GATHER);
        return;
    }


    const int q4 = lane & 3, g8 = lane >> 2;
    const int rowT = (lane & 7) + ((lane >> 4) << 3), hiT = (lane >> 3) & 1;
    const uint32_t off_v = ((3 * rowT + (warp >> 1)) * 128 + ((hiT ^ ((3 * rowT + (warp >> 1)) & 7)) << 4)) ^ ((warp & 1) << 6);

    if (warp < V_WARPS) {
#pragma unroll 1
        for (int part = 0; part <= tri; part++) {
            const uint32_t xa = sb + SM_XN + ((part ? rank * 16 - 1280 : (rank & 3) * 16) + 2 * q4) * 2, xs = 128 << part;
            float acc[2][4] = {};
#pragma unroll 1
            for (int p = part * 10; p < 10 + part * 5; p++) {
                const uint32_t b0 = lds32(xa + p * xs), b1 = lds32(xa + p * xs + 16);
                mbar_wait(bar_full + (p >> 1) * 8, 0);
                uint32_t a[4];
                ldsm_x4_t(a, sb + SM_RING + p * PIECE_BYTES + off_v);
                mma_bf16(acc[0], a, b0, b1);
                ldsm_x4_t(a, sb + SM_RING + p * PIECE_BYTES + (off_v ^ 32));
                mma_bf16(acc[1], a, b0, b1);
                __syncwarp();
                if (lane == 0) mbar_arrive_n(bar_empty + (p >> 1) * 8, p == 14 ? RELEASE / V_WARPS : RELEASE / V_WARPS / 2);
            }
            const float v = pick4(acc[0][0], acc[0][2], acc[1][0], acc[1][2], q4);
            const uint32_t dst = sb + SM_QP + ((part * CL + rank) * D_HEAD + warp * 32 + q4 * 8 + g8) * 4;
#pragma unroll
            for (int d = 0; d < CL; d++) st_async(mapa(dst, d), v, mapa(bar + BAR_Q, d));
        }
        mbar_wait(bar + BAR_Q, 0);
        const float* qp = reinterpret_cast<const float*>(sp + SM_QP) + tid;
        __nv_bfloat16* qs = reinterpret_cast<__nv_bfloat16*>(sp + SM_Q) + tid;
        qs[0] = __float2bfloat16_rn((qp[0] + qp[192]) + (qp[384] + qp[576]));
        qs[(tri + 1) * D_HEAD] = __float2bfloat16_rn((qp[768] + qp[960]) + (qp[1152] + qp[1344]));
        if (tri) {
            qp += CL * D_HEAD;
            qs[D_HEAD] = __float2bfloat16_rn(((qp[0] + qp[192]) + (qp[384] + qp[576])) + ((qp[768] + qp[960]) + (qp[1152] + qp[1344])));
        }
    }
    named_sync(1, N_CONS);

    {
        const int rowN = (lane & 7) + (((lane >> 3) & 1) << 3), hiN = lane >> 4;
#pragma unroll 1
        for (int hh = 0; hh < n_heads; hh++) {
            float s0 = 0.f, s1 = 0.f;
#pragma unroll 1
            for (int i = 0; i < 2; i++) {
                const int u = hh * HEAD_TILES + i * 8 + warp, pos = pos_k + u, slot = pos & (N_SLOT - 1);
                mbar_wait(bar_full + slot * 8, (pos >> 4) & 1);
                const uint32_t tb = sb + SM_RING + slot * TILE_BYTES;
                float acc[2][2][4] = {};
#pragma unroll 1
                for (int j = 0; j < 3; j++) {
                    const int swz = u < 2 ? 0 : (3 * rowN + j) & 7;
                    const uint32_t oj = tb + (3 * rowN + j) * 128 + ((hiN ^ swz) << 4);
                    const uint32_t qa = sb + SM_Q + (hh * D_HEAD + j * 64 + 2 * q4) * 2;
#pragma unroll
                    for (int k = 0; k < 4; k++) {
                        const uint32_t b0 = lds32(qa + k * 32), b1 = lds32(qa + k * 32 + 16);
                        uint32_t a[4];
                        ldsm_x4(a, oj ^ (k << 5));
                        mma_bf16(acc[0][k & 1], a, b0, b1);
                        ldsm_x4(a, (oj + PIECE_BYTES) ^ (k << 5));
                        mma_bf16(acc[1][k & 1], a, b0, b1);
                    }
                }
                __syncwarp();
                if (lane == 0) mbar_arrive_n(bar_empty + slot * 8, RELEASE);
                const float raw = pick4(acc[0][0][0] + acc[0][1][0], acc[0][0][2] + acc[0][1][2],
                                        acc[1][0][0] + acc[1][1][0], acc[1][0][2] + acc[1][1][2], q4);
                s0 = s1;
                s1 = bf16r(bf16r(raw) * 0.07216878364870323f);
            }
            float m = fmaxf(s0, s1);
#pragma unroll
            for (int o = 16; o > 0; o >>= 1) m = fmaxf(m, __shfl_xor_sync(0xffffffffu, m, o));
            if (lane == 0) sst[hh * 8 + warp] = m;
            named_sync(1, N_CONS);
#pragma unroll
            for (int w = 0; w < 8; w++) m = fmaxf(m, sst[hh * 8 + w]);
            const float p0 = ex2((s0 - m) * LOG2E), p1 = ex2((s1 - m) * LOG2E);
            float l = p0 + p1;
#pragma unroll
            for (int o = 16; o > 0; o >>= 1) l += __shfl_xor_sync(0xffffffffu, l, o);
            if (lane == 0) sst[24 + hh * 8 + warp] = l;
            __nv_bfloat16* ps = reinterpret_cast<__nv_bfloat16*>(sp + SM_P) + hh * 512 + warp * 32 + q4 * 8 + g8;
            ps[0] = __float2bfloat16_rn(p0);
            ps[256] = __float2bfloat16_rn(p1);
        }
        named_sync(1, N_CONS);
        if (warp == 7 && lane < n_heads * CL && (lane & 7) < V_WARPS) {
            const float* st = sst + (lane & 24);
            float m = st[0], l = st[24];
#pragma unroll
            for (int w = 1; w < 8; w++) { m = fmaxf(m, st[w]); l += st[24 + w]; }
            st_async2(mapa(sb + SM_ML + ((lane & 24) + rank) * 8, lane & 7), m, l, mapa(bar + BAR_ML, lane & 7));
        }
    }

    const uint32_t off_w = (warp >> 2) * PIECE_BYTES + rowT * 128 + (((((warp & 3) << 1) | hiT) ^ (rowT & 7)) << 4);

    if (ffn) {
#pragma unroll 1
        for (int res = 0; res < 2; res++) {
            float acc[3][4] = {};
#pragma unroll 1
            for (int i = 0; i < W_TILES / 2; i++) {
                const int pos = pos_w + res * (W_TILES / 2) + i, slot = pos & (N_SLOT - 1);
                const uint32_t xa = sb + SM_XN + (i * 96 + (warp >> 2) * 48 + 2 * q4) * 2;
                mbar_wait(bar_full + slot * 8, (pos >> 4) & 1);
#pragma unroll
                for (int k = 0; k < 3; k++) {
                    uint32_t a[4];
                    ldsm_x4_t(a, sb + SM_RING + slot * TILE_BYTES + off_w + k * 2048);
                    mma_bf16(acc[k], a, lds32(xa + k * 32), lds32(xa + k * 32 + 16));
                }
                __syncwarp();
                if (lane == 0) mbar_arrive_n(bar_empty + slot * 8, RELEASE / N_CONS_WARPS);
            }
            if (q4 < 2)
                reinterpret_cast<float*>(sp + SM_FG)[res * 128 + warp * 16 + q4 * 8 + g8] =
                    q4 ? (acc[0][2] + acc[1][2]) + acc[2][2] : (acc[0][0] + acc[1][0]) + acc[2][0];
        }
        named_sync(1, N_CONS);
        if (warp >= V_WARPS) {
            const float* f = reinterpret_cast<const float*>(sp + SM_FG) + (tid & 63);
            const float h = bf16r(bf16r(silu_f(bf16r(f[0] + f[64]))) * bf16r(f[128] + f[192]));
            ll_store(g_x + (cta - CL_FFN * CL) * 64 + (tid & 63), __float_as_uint(h) | tag);
        }
    }

    if (warp < V_WARPS) {
        const uint32_t rdst = mapa(sb + SM_OP + rank * 128 + (q4 * 8 + g8) * 4, warp), rbar = mapa(bar + BAR_O, warp);
#pragma unroll 1
        for (int hh = 0; hh < n_heads; hh++) {
            float oacc[2][2][4] = {};
#pragma unroll 2
            for (int u = hh * HEAD_TILES; u < (hh + 1) * HEAD_TILES; u++) {
                const int pos = pos_v + u, slot = pos & (N_SLOT - 1);
                uint32_t ta = sb + SM_RING + slot * TILE_BYTES + off_v, tc = ta ^ 32;
                asm volatile("" : "+r"(ta), "+r"(tc));
                const uint32_t pa = sb + SM_P + (u * 32 + 2 * q4) * 2;
                const uint32_t b0 = lds32(pa), b1 = lds32(pa + 16), b2 = lds32(pa + 32), b3 = lds32(pa + 48);
                mbar_wait(bar_full + slot * 8, (pos >> 4) & 1);
                uint32_t a[4][4];
                ldsm_x4_t(a[0], ta);
                ldsm_x4_t(a[1], tc);
                ldsm_x4_t(a[2], ta + PIECE_BYTES);
                ldsm_x4_t(a[3], tc + PIECE_BYTES);
                mma_bf16(oacc[0][0], a[0], b0, b1);
                mma_bf16(oacc[1][0], a[1], b0, b1);
                mma_bf16(oacc[0][1], a[2], b2, b3);
                mma_bf16(oacc[1][1], a[3], b2, b3);
                __syncwarp();
                if (lane == 0) mbar_arrive_n(bar_empty + slot * 8, RELEASE / V_WARPS);
            }
            const float v = pick4(oacc[0][0][0] + oacc[0][1][0], oacc[0][0][2] + oacc[0][1][2],
                                  oacc[1][0][0] + oacc[1][1][0], oacc[1][0][2] + oacc[1][1][2], q4);
            st_async(rdst + hh * 1024, v, rbar + hh * 8);
        }
    }
    if (!owner) return;

    {
        constexpr int P0 = POS_K2 + 4 * HEAD_TILES;
        const uint32_t rdst = mapa(sb + SM_FG + (rank * 2 + (warp >> 2)) * 64 + g8 * 8, warp & 3);
        const uint32_t rbar = mapa(bar + BAR_G, warp & 3);
        const uint32_t va = sb + SM_OV + ((warp >> 2) * 48 + 2 * q4) * 2, tw = sb + SM_RING + off_w;
        named_sync(8, N_CONS + N_GATHER);
        auto send = [&](const float (&acc)[3][4], uint32_t dst, uint32_t mb) {
            if (q4 == 0) st_async2(dst, (acc[0][0] + acc[1][0]) + acc[2][0], (acc[0][2] + acc[1][2]) + acc[2][2], mb);
        };
        float acc[3][4] = {};
#pragma unroll 1
        for (int i = 0; i < 6; i++) {
            const int slot = (P0 + i) & (N_SLOT - 1);
            uint32_t b[3][2];
#pragma unroll
            for (int k = 0; k < 3; k++) { b[k][0] = lds32(va + i * 192 + k * 32); b[k][1] = lds32(va + i * 192 + k * 32 + 16); }
            mbar_wait(bar_full + slot * 8, ((P0 + i) >> 4) & 1);
#pragma unroll
            for (int k = 0; k < 3; k++) {
                uint32_t a[4];
                ldsm_x4_t(a, tw + slot * TILE_BYTES + k * 2048);
                mma_bf16(acc[k], a, b[k][0], b[k][1]);
            }
            if (i == 1) {
                send(acc, rdst, rbar);
#pragma unroll
                for (int k = 0; k < 3; k++) acc[k][0] = acc[k][1] = acc[k][2] = acc[k][3] = 0.f;
            }
        }
        static_assert(((P0 + 6) >> 4) % 2 == 0 && (P0 + 9) >> 4 == (P0 + 6) >> 4, "both kinds of barrier complete a phase of parity 0");
        const uint32_t hb = warp < 4 ? bar_full + ((P0 + 6) & (N_SLOT - 1)) * 8 : bar + BAR_HALF;
        uint32_t a[4][3][4], b[4][3][2];
        named_sync(3, N_CONS + N_GATHER);
#pragma unroll
        for (int i = 0; i < 4; i++)
#pragma unroll
            for (int k = 0; k < 3; k++) { b[i][k][0] = lds32(va + (6 + i) * 192 + k * 32); b[i][k][1] = lds32(va + (6 + i) * 192 + k * 32 + 16); }
#pragma unroll
        for (int i = 0; i <= 4; i++) {
            if (i < 4) {
                const int slot = (P0 + 6 + i) & (N_SLOT - 1);
                mbar_wait(hb + i * 8, 0);
#pragma unroll
                for (int k = 0; k < 3; k++) ldsm_x4_t(a[i][k], tw + slot * TILE_BYTES + k * 2048);
            }
            if (i >= 1) {
#pragma unroll
                for (int k = 0; k < 3; k++) mma_bf16(acc[k], a[i - 1][k], b[i - 1][k][0], b[i - 1][k][1]);
            }
        }
        send(acc, rdst + (SM_FS - SM_FG), rbar + (BAR_S - BAR_G));
    }
}

typedef CUresult (*EncodeTiledFn)(CUtensorMap*, CUtensorMapDataType, cuuint32_t, void*, const cuuint64_t*,
                                  const cuuint64_t*, const cuuint32_t*, const cuuint32_t*, CUtensorMapInterleave,
                                  CUtensorMapSwizzle, CUtensorMapL2promotion, CUtensorMapFloatOOBfill);

void encode_map(EncodeTiledFn fn, CUtensorMap* m, const void* base, cuuint64_t rows, cuuint64_t cols, cuuint32_t b1, cuuint32_t b2) {
    const cuuint64_t dims[3] = {64, cols / 64, rows};
    const cuuint64_t strides[2] = {128, cols * 2};
    const cuuint32_t box[3] = {64, b1, b2};
    const cuuint32_t estr[3] = {1, 1, 1};
    fn(m, CU_TENSOR_MAP_DATA_TYPE_BFLOAT16, 3, const_cast<void*>(base), dims, strides, box, estr,
       CU_TENSOR_MAP_INTERLEAVE_NONE, CU_TENSOR_MAP_SWIZZLE_128B, CU_TENSOR_MAP_L2_PROMOTION_NONE,
       CU_TENSOR_MAP_FLOAT_OOB_FILL_NONE);
}

}

extern "C" void kernel_launch(void* const* d_in, const int* in_sizes, int n_in, void* d_out, int out_size) {
    (void)in_sizes; (void)n_in; (void)out_size;
    static EncodeTiledFn encode = nullptr;
    static double pace_scale = 1.0;
    static void* scratch = nullptr;
    if (!encode) {
        int dev = 0, mem_khz = 0, bus_bits = 0;
        cudaGetDevice(&dev);
        cudaDeviceGetAttribute(&mem_khz, cudaDevAttrMemoryClockRate, dev);
        cudaDeviceGetAttribute(&bus_bits, cudaDevAttrGlobalMemoryBusWidth, dev);
        const double peak_gbs = 2.0 * mem_khz * 1e-6 * bus_bits / 8.0;
        if (peak_gbs > 0.0) pace_scale = PACE_REF_GBS / peak_gbs;
        void* fn = nullptr;
        cudaDriverEntryPointQueryResult qr;
        cudaGetDriverEntryPoint("cuTensorMapEncodeTiled", &fn, cudaEnableDefault, &qr);
        encode = reinterpret_cast<EncodeTiledFn>(fn);
        cudaFuncSetAttribute(fused_decode_kernel, cudaFuncAttributeMaxDynamicSharedMemorySize, SM_ALLOC);
        cudaGetSymbolAddress(&scratch, g_scratch);
    }
    CUtensorMap tm_k, tm_v, tm_wq, tm_w1, tm_w3, tm_wo, tm_w2;
    encode_map(encode, &tm_k, d_in[1], (cuuint64_t)N_HEAD * SEQ, D_HEAD, 3, 32);
    encode_map(encode, &tm_v, d_in[2], (cuuint64_t)N_HEAD * SEQ, D_HEAD, 3, 32);
    encode_map(encode, &tm_wq, d_in[3], D_MODEL, N_HEAD * D_HEAD, 3, 16);
    encode_map(encode, &tm_w1, d_in[6], D_MODEL, D_FF, 1, 96);
    encode_map(encode, &tm_w3, d_in[7], D_MODEL, D_FF, 1, 96);
    encode_map(encode, &tm_wo, d_in[4], N_HEAD * D_HEAD, D_MODEL, 1, 48);
    encode_map(encode, &tm_w2, d_in[8], D_FF, D_MODEL, 1, 48);
    Params prm;
    prm.x = static_cast<const __nv_bfloat16*>(d_in[0]);
    prm.out = static_cast<__nv_bfloat16*>(d_out);
    prm.k = static_cast<const __nv_bfloat16*>(d_in[1]) + (size_t)(SEQ - WIN) * D_HEAD;
    prm.scratch = static_cast<uint32_t*>(scratch);
    auto step = [&](double pace, double bytes, int pieces) { return (uint16_t)(8.0 * pace * pace_scale * bytes / (128.0 * TILE_BYTES) / pieces); };
    const double b_wq = 2.0 * D_MODEL * N_HEAD * D_HEAD;
    const double b_mid = 4.0 * N_HEAD * WIN * D_HEAD - 2.0 * N_CTA * TILE_BYTES + 4.0 * D_MODEL * D_FF;
    const double b_tail = 2.0 * D_MODEL * (D_FF + N_HEAD * D_HEAD);
    prm.step_wq2 = step(PACE_HEAD, b_wq, 10);
    prm.step_wq3 = step(PACE_HEAD, b_wq, 15);
    prm.step_own = step(PACE_MID, b_mid, 4 * HEAD_TILES - 2);
    prm.step_ffn = step(PACE_MID, b_mid, 4 * HEAD_TILES - 2 + W_TILES);
    prm.step_tri = step(PACE_MID, b_mid, 6 * HEAD_TILES - 2);
    prm.step_tail = step(PACE_TAIL, b_tail, TAIL_TILES);
    prm.late = (uint16_t)(4096.0 * PACE_LATE / PACE_MID + 0.5);
    prm.pad = 0;
    fused_decode_kernel<<<N_CTA, N_THREADS, SM_ALLOC, cudaStreamPerThread>>>(prm, tm_wq, tm_w1, tm_w3, tm_k, tm_v, tm_wo, tm_w2);
}
```

```cpp
#include <cuda_runtime.h>
#include <cuda_bf16.h>
#include <cuda.h>
#include <stdint.h>

namespace {

constexpr int D_MODEL = 640;
constexpr int N_HEAD = 32;
constexpr int D_HEAD = 192;
constexpr int SEQ = 32768;
constexpr int WIN = 4096;
constexpr int D_FF = 1536;

constexpr int CL = 8;
constexpr int N_CL = 15;
constexpr int N_CTA = CL * N_CL;
constexpr int CL_FFN = 1, CL_TRI = CL_FFN + 3, CL_OWN = CL_TRI + 2;
constexpr int TILE_BYTES = 12288;
constexpr int PIECE_BYTES = TILE_BYTES / 2;
constexpr int N_SLOT = 16;
constexpr int HEAD_TILES = WIN / CL / 32;
constexpr int W_TILES = 14;
constexpr int TAIL_TILES = 10;
constexpr int POS_K2 = 5, POS_K3 = 8;

constexpr int N_CONS_WARPS = 8;
constexpr int N_CONS = N_CONS_WARPS * 32;
constexpr int N_GATHER = 128;
constexpr int N_THREADS = N_CONS + 64 + N_GATHER;
constexpr int V_WARPS = 6;
constexpr int RELEASE = 24;

constexpr double PACE_HEAD = 490, PACE_MID = 479, PACE_LATE = 495, PACE_TAIL = 482, PACE_REF_GBS = 3352.32;
constexpr int START_DELAY = 140;
constexpr int WINDOW_OWN = 5, WINDOW_FFN = 6, WINDOW_FAST = 8;
constexpr int SLIP = 50;
constexpr int GATE_EARLY = 4, GATE_LATE = 7;

constexpr unsigned SPIN_LIMIT = 1u << 22;

constexpr int SM_RING = 0;
constexpr int SM_BAR = N_SLOT * TILE_BYTES;
constexpr int BAR_FULL = 0, BAR_EMPTY = 128, BAR_GO = 256, BAR_Q = 272, BAR_ML = 280, BAR_O = 288, BAR_G = 312, BAR_S = 320, BAR_X = 328,
              BAR_HALF = 336, BAR_READY = 368;
constexpr int SM_T0 = SM_BAR + 448, SM_EPOCH = SM_BAR + 452;
constexpr int SM_XN = SM_BAR + 512;
constexpr int SM_Q = SM_XN + 1408;
constexpr int SM_ST = SM_Q + 1152;
constexpr int SM_ML = SM_ST + 256;
constexpr int SM_P = SM_ML + 256;
constexpr int SM_QP = SM_P + 3072;
constexpr int SM_OP = SM_QP + 12288;
constexpr int SM_OV = SM_OP + 3072;
constexpr int SM_FG = SM_OV + 1920;
constexpr int SM_FS = SM_FG + 1024;
constexpr int SM_ALLOC = SM_FS + 1024 + 1024;

constexpr int XO_H = 32;
constexpr int XO_END = XO_H + D_FF + N_HEAD * D_HEAD;
__device__ __align__(128) uint32_t g_scratch[XO_END];

__device__ __forceinline__ uint32_t smem_u32(const void* p) { return (uint32_t)__cvta_generic_to_shared(p); }

__device__ __forceinline__ void mbar_init(uint32_t bar, uint32_t cnt) {
    asm volatile("mbarrier.init.shared::cta.b64 [%0], %1;" ::"r"(bar), "r"(cnt) : "memory");
}
__device__ __forceinline__ void mbar_expect_tx(uint32_t bar, uint32_t bytes) {
    asm volatile("mbarrier.arrive.expect_tx.shared::cta.b64 _, [%0], %1;" ::"r"(bar), "r"(bytes) : "memory");
}
__device__ __forceinline__ void mbar_arrive(uint32_t bar) {
    asm volatile("mbarrier.arrive.shared::cta.b64 _, [%0];" ::"r"(bar) : "memory");
}
__device__ __forceinline__ void mbar_wait(uint32_t bar, uint32_t parity) {
    asm volatile(
        "{\n.reg .pred p, q;\n.reg .u32 n;\n"
        "mov.u32 n, 0;\n"
        "WAIT_LOOP:\n"
        "add.u32 n, n, 1;\n"
        "setp.lt.u32 q, n, %2;\n"
        "mbarrier.try_wait.parity.shared::cta.b64 p, [%0], %1;\n"
        "and.pred q, q, !p;\n"
        "@q bra WAIT_LOOP;\n}"
        ::"r"(bar), "r"(parity), "n"(SPIN_LIMIT) : "memory");
}
__device__ __forceinline__ void named_sync(int id, int n) {
    asm volatile("bar.sync %0, %1;" ::"r"(id), "r"(n) : "memory");
}
__device__ __forceinline__ void named_arrive(int id, int n) {
    asm volatile("bar.arrive %0, %1;" ::"r"(id), "r"(n) : "memory");
}
__device__ __forceinline__ uint64_t stream_policy() {
    uint64_t pol;
    asm volatile("createpolicy.fractional.L2::evict_first.b64 %0, 1.0;" : "=l"(pol));
    return pol;
}
__device__ __forceinline__ void bulk_load(uint32_t dst, const void* src, uint32_t bytes, uint32_t bar, uint64_t pol) {
    asm volatile("cp.async.bulk.shared::cluster.global.mbarrier::complete_tx::bytes.L2::cache_hint [%0], [%1], %2, [%3], %4;"
                 ::"r"(dst), "l"(src), "r"(bytes), "r"(bar), "l"(pol) : "memory");
}
__device__ __forceinline__ void tma_3d(uint32_t dst, const CUtensorMap* tm, int c0, int c1, int c2, uint32_t bar, uint64_t pol) {
    asm volatile("cp.async.bulk.tensor.3d.shared::cluster.global.mbarrier::complete_tx::bytes.L2::cache_hint [%0], [%1, {%3, %4, %5}], [%2], %6;"
                 ::"r"(dst), "l"(tm), "r"(bar), "r"(c0), "r"(c1), "r"(c2), "l"(pol) : "memory");
}
__device__ __forceinline__ void prefetch_tmap(const CUtensorMap* tm) {
    asm volatile("prefetch.tensormap [%0];" ::"l"(tm) : "memory");
}
__device__ __forceinline__ void ldsm_x4(uint32_t (&r)[4], uint32_t addr) {
    asm volatile("ldmatrix.sync.aligned.m8n8.x4.shared.b16 {%0,%1,%2,%3}, [%4];"
                 : "=r"(r[0]), "=r"(r[1]), "=r"(r[2]), "=r"(r[3]) : "r"(addr) : "memory");
}
__device__ __forceinline__ void ldsm_x4_t(uint32_t (&r)[4], uint32_t addr) {
    asm volatile("ldmatrix.sync.aligned.m8n8.x4.trans.shared.b16 {%0,%1,%2,%3}, [%4];"
                 : "=r"(r[0]), "=r"(r[1]), "=r"(r[2]), "=r"(r[3]) : "r"(addr) : "memory");
}
__device__ __forceinline__ void mma_bf16(float (&c)[4], const uint32_t (&a)[4], uint32_t b0, uint32_t b1) {
    asm volatile("mma.sync.aligned.m16n8k16.row.col.f32.bf16.bf16.f32 {%0,%1,%2,%3}, {%4,%5,%6,%7}, {%8,%9}, {%0,%1,%2,%3};"
                 : "+f"(c[0]), "+f"(c[1]), "+f"(c[2]), "+f"(c[3])
                 : "r"(a[0]), "r"(a[1]), "r"(a[2]), "r"(a[3]), "r"(b0), "r"(b1));
}
__device__ __forceinline__ float bf16r(float v) {
    uint32_t p;
    asm("cvt.rn.bf16x2.f32 %0, %1, %2;" : "=r"(p) : "f"(v), "f"(0.f));
    return __uint_as_float(p);
}
__device__ __forceinline__ uint32_t lds32(uint32_t addr) {
    uint32_t v;
    asm volatile("ld.shared.b32 %0, [%1];" : "=r"(v) : "r"(addr) : "memory");
    return v;
}
__device__ __forceinline__ float bf_lo(uint32_t v) { return __uint_as_float(v << 16); }
__device__ __forceinline__ float bf_hi(uint32_t v) { return __uint_as_float(v & 0xffff0000u); }
__device__ __forceinline__ uint32_t pack_bf16(float lo, float hi) {
    const __nv_bfloat162 p = __floats2bfloat162_rn(lo, hi);
    return *reinterpret_cast<const uint32_t*>(&p);
}
__device__ __forceinline__ uint32_t now_ns() {
    unsigned long long t;
    asm volatile("mov.u64 %0, %%globaltimer;" : "=l"(t));
    return (uint32_t)t;
}

__device__ __forceinline__ void wait_until(uint32_t t_start, uint32_t deadline) {
    unsigned n = 0;
    while (now_ns() - t_start < deadline && ++n < SPIN_LIMIT) {}
}

__device__ __forceinline__ uint32_t ll_bad4(const uint4& v, uint32_t tag) {
    uint32_t lo, hi;
    asm("lop3.b32 %0, %1, %2, %3, 0x7E;" : "=r"(lo) : "r"(v.x), "r"(v.y), "r"(tag));
    asm("lop3.b32 %0, %1, %2, %3, 0x7E;" : "=r"(hi) : "r"(v.z), "r"(v.w), "r"(tag));
    return (lo | hi) & 3u;
}
__device__ __forceinline__ float ex2(float v) {
    float r;
    asm("ex2.approx.ftz.f32 %0, %1;" : "=f"(r) : "f"(v));
    return r;
}
__device__ __forceinline__ float rcp(float v) {
    float r;
    asm("rcp.approx.ftz.f32 %0, %1;" : "=f"(r) : "f"(v));
    return r;
}
constexpr float LOG2E = 1.4426950408889634f;
__device__ __forceinline__ void ll_store(uint32_t* p, uint32_t w) {
    asm volatile("st.relaxed.gpu.global.b32 [%0], %1;" ::"l"(p), "r"(w) : "memory");
}
__device__ __forceinline__ uint32_t ll_ld(const uint32_t* p) {
    uint32_t v;
    asm volatile("ld.relaxed.gpu.global.b32 %0, [%1];" : "=r"(v) : "l"(p) : "memory");
    return v;
}
__device__ __forceinline__ float pick4(float a, float b, float c, float d, int j) {
    const float lo = (j & 1) ? b : a, hi = (j & 1) ? d : c;
    return (j & 2) ? hi : lo;
}
__device__ __forceinline__ float silu_f(float v) { return v * rcp(1.f + ex2(-LOG2E * v)); }

__device__ __forceinline__ void mbar_arrive_n(uint32_t bar, uint32_t n) {
    asm volatile("mbarrier.arrive.shared::cta.b64 _, [%0], %1;" ::"r"(bar), "r"(n) : "memory");
}
__device__ __forceinline__ uint32_t mapa(uint32_t addr, uint32_t rank) {
    uint32_t d;
    asm("mapa.shared::cluster.u32 %0, %1, %2;" : "=r"(d) : "r"(addr), "r"(rank));
    return d;
}
__device__ __forceinline__ void st_async(uint32_t dst, float v, uint32_t bar) {
    asm volatile("st.async.weak.shared::cluster.mbarrier::complete_tx::bytes.f32 [%0], %1, [%2];" ::"r"(dst), "f"(v), "r"(bar) : "memory");
}
__device__ __forceinline__ void st_async2(uint32_t dst, float a, float b, uint32_t bar) {
    asm volatile("st.async.weak.shared::cluster.mbarrier::complete_tx::bytes.v2.f32 [%0], {%1, %2}, [%3];" ::"r"(dst), "f"(a), "f"(b), "r"(bar) : "memory");
}
__device__ __forceinline__ void cluster_arrive() { asm volatile("barrier.cluster.arrive.relaxed.aligned;" ::: "memory"); }
__device__ __forceinline__ void cluster_wait() { asm volatile("barrier.cluster.wait.aligned;" ::: "memory"); }
__device__ __forceinline__ void ll_ld4_if(uint4& v, const uint32_t* p, uint32_t cond) {
    asm volatile("{\n.reg .pred p;\nsetp.ne.u32 p, %5, 0;\n@p ld.relaxed.gpu.global.v4.b32 {%0,%1,%2,%3}, [%4];\n}"
                 : "+r"(v.x), "+r"(v.y), "+r"(v.z), "+r"(v.w) : "l"(p), "r"(cond) : "memory");
}
__device__ __forceinline__ float lds_f(uint32_t addr) { return __uint_as_float(lds32(addr)); }
__device__ __forceinline__ float lds_colsum(uint32_t base, int lane) {
    const uint32_t addr = base + ((lane >> 3) ^ ((lane >> 2) & 1)) * 64 + (lane & 3) * 16;
    uint32_t v[4][4];
#pragma unroll
    for (int i = 0; i < 4; i++) ldsm_x4(v[i], addr + i * 256);
    float t[4];
#pragma unroll
    for (int i = 0; i < 4; i++)
        t[i] = (__uint_as_float(v[i][0]) + __uint_as_float(v[i][1])) + (__uint_as_float(v[i][2]) + __uint_as_float(v[i][3]));
    return ((t[0] + t[1]) + t[2]) + t[3];
}

constexpr uint32_t FIRST_MUL = 257, FIRST_MASK = 0x7807;
__device__ __forceinline__ int pair_head(int cl, int j) { return 2 * cl + j; }
__device__ __forceinline__ int third_head(int cl) { return 2 * N_CL + cl - CL_TRI; }
__device__ __forceinline__ int head_at(int cl, int hh, int tri) { return (hh & tri) ? third_head(cl) : pair_head(cl, hh >> tri); }
__device__ __forceinline__ int tail_row(int rank, int i) {
    if (i < 2) return i * 768 + rank * 96;
    const int j = 4 * (i - 2) + (rank >> 1), q = rank & 1;
    return D_FF + (2 * (j & 15) + (j >> 4)) * D_HEAD + q * 96;
}

struct Params {
    const __nv_bfloat16* x;
    __nv_bfloat16* out;
    const __nv_bfloat16* k;
    uint32_t* scratch;
    uint16_t step_wq2, step_wq3, step_own, step_ffn, step_tri, step_tail, late, pad;
};
static_assert(sizeof(Params) == 48, "Params must fill the rest of the first parameter line");

__global__ void __cluster_dims__(CL, 1, 1) __launch_bounds__(N_THREADS, 1)
fused_decode_kernel(const Params prm, const __grid_constant__ CUtensorMap tm_wq, const __grid_constant__ CUtensorMap tm_w1,
                    const __grid_constant__ CUtensorMap tm_w3, const __grid_constant__ CUtensorMap tm_k,
                    const __grid_constant__ CUtensorMap tm_v, const __grid_constant__ CUtensorMap tm_wo,
                    const __grid_constant__ CUtensorMap tm_w2) {
    extern __shared__ uint8_t smem_raw[];
    asm volatile("{\n.reg .pred p;\nsetp.lt.u32 p, %1, %2;\n@p prefetch.global.L2 [%0];\n}"
                 ::"l"(reinterpret_cast<const char*>(prm.k) + (size_t)(((blockIdx.x * FIRST_MUL) & FIRST_MASK) * (TILE_BYTES / 32) + threadIdx.x) * 32),
                   "r"(threadIdx.x), "n"(TILE_BYTES / 32) : "memory");
    const uint32_t sb = (smem_u32(smem_raw) + 1023u) & ~1023u;
    uint8_t* sp = smem_raw + (sb - smem_u32(smem_raw));
    const uint32_t bar = sb + SM_BAR;
    const uint32_t bar_full = bar + BAR_FULL, bar_empty = bar + BAR_EMPTY;

    const int tid = threadIdx.x;
    const int cta = blockIdx.x, cl = blockIdx.x / CL, rank = blockIdx.x % CL;
    const int tri = cl >= CL_TRI && cl < CL_OWN;
    const int pos_k = tri ? POS_K3 : POS_K2;
    volatile uint32_t* t_first = reinterpret_cast<volatile uint32_t*>(sp + SM_T0);
    if (tid == N_CONS) {
        const __nv_bfloat16* k0 = prm.k + (uint32_t)(pair_head(cl, 0) * SEQ + rank * 32) * (size_t)D_HEAD;
#pragma unroll
        for (int u = 1; u >= 0; u--) {
            const uint32_t fb = bar_full + (pos_k + u) * 8;
            mbar_init(fb, 1);
            asm volatile("fence.mbarrier_init.release.cluster;" ::: "memory");
            mbar_expect_tx(fb, TILE_BYTES);
            bulk_load(sb + SM_RING + (pos_k + u) * TILE_BYTES, k0 + u * (CL * 32 * D_HEAD), TILE_BYTES, fb, stream_policy());
            if (u == 1) *t_first = now_ns();
        }
    }
    if (tid == N_CONS + 32) prefetch_tmap(&tm_wq);
    const int warp = __shfl_sync(0xffffffffu, tid >> 5, 0), lane = tid & 31;
    const bool owner = cl < CL_FFN || cl >= CL_OWN, ffn = !owner && !tri;
    const int oc = cl < CL_FFN ? cl : cl - (CL_OWN - CL_FFN);
    const int n_heads = 2 + tri;
    const int pos_w = pos_k + n_heads * HEAD_TILES;
    const int pos_v = pos_w + (ffn ? W_TILES : 0);
    const int pos_t = pos_v + n_heads * HEAD_TILES;
    uint32_t* const g_epoch = prm.scratch;
    uint32_t* const g_x = prm.scratch + XO_H;
    const int n_start = owner ? N_THREADS : N_THREADS - 96;

    if (warp == N_CONS_WARPS) {
        if (lane == 0) {
#pragma unroll
            for (int i = 2; i < N_SLOT; i++) mbar_init(bar_full + ((pos_k + i) & (N_SLOT - 1)) * 8, 1);
            mbar_init(bar + BAR_READY, 1);
            asm volatile("fence.mbarrier_init.release.cluster;" ::: "memory");
        }
        __syncwarp();
        named_arrive(6, n_start);
        cluster_arrive();
        if (lane == 0) {
            const uint64_t pol = stream_policy();
            const uint32_t t_start = *t_first;
            uint32_t deadline = START_DELAY * 8;
            {
                const uint32_t step = tri ? prm.step_wq3 : prm.step_wq2;
#pragma unroll 1
                for (int p = 0; p < 10 + 5 * tri; p++) {
                    const uint32_t fb = bar_full + (p >> 1) * 8;
                    if (!(p & 1)) mbar_expect_tx(fb, p == 14 ? PIECE_BYTES : TILE_BYTES);
                    const int h = p < 10 ? pair_head(cl, rank >> 2) : third_head(cl);
                    const int row = p < 10 ? p * 64 + (rank & 3) * 16 : (p - 10) * 128 + rank * 16;
                    wait_until(t_start, deadline >> 3);
                    tma_3d(sb + SM_RING + p * PIECE_BYTES, &tm_wq, 0, h * 3, row, fb, pol);
                    deadline += step;
                }
            }
            mbar_wait(bar + BAR_READY, 0);
            uint32_t step = owner ? prm.step_own : (tri ? prm.step_tri : prm.step_ffn);
            int window = owner ? WINDOW_OWN : (tri ? WINDOW_FAST : WINDOW_FFN);
            const int pos_end = pos_t + (owner ? TAIL_TILES : 0);
            const int pos_late = pos_t - (owner ? 16 : (tri ? 24 : 20));
#pragma unroll 1
            for (int pos = pos_k + 2; pos < pos_end; pos++) {
                const int slot = pos & (N_SLOT - 1);
                const CUtensorMap* tm;
                int c1 = 0, row;
                if (pos >= pos_t) {
                    step = prm.step_tail;
                    window = WINDOW_FAST;
                    row = tail_row(rank, pos - pos_t);
                    tm = row < D_FF ? &tm_w2 : &tm_wo;
                    if (row >= D_FF) row -= D_FF;
                    c1 = oc;
                } else if (pos >= pos_w && pos < pos_v) {
                    const bool up = pos >= pos_w + W_TILES / 2;
                    tm = up ? &tm_w3 : &tm_w1;
                    c1 = cta - CL_FFN * CL;
                    row = (pos - pos_w - (up ? W_TILES / 2 : 0)) * 96;
                } else {
                    const int u = pos - (pos < pos_w ? pos_k : pos_v), hh = u >> 4;
                    tm = pos < pos_w ? &tm_k : &tm_v;
                    row = head_at(cl, hh, tri) * SEQ + (SEQ - WIN) + rank * 32 + (u & 15) * (CL * 32);
                }
                if (pos >= N_SLOT) mbar_wait(bar_empty + slot * 8, ((pos >> 4) - 1) & 1);
                if (pos >= pos_k + 2 + window) mbar_wait(bar_full + ((pos - window) & (N_SLOT - 1)) * 8, ((pos - window) >> 4) & 1);
                deadline = max(deadline, (now_ns() - t_start - SLIP) << 3);
                mbar_expect_tx(bar_full + slot * 8, pos >= pos_t + 6 ? PIECE_BYTES : TILE_BYTES);
                wait_until(t_start, deadline >> 3);
                tma_3d(sb + SM_RING + slot * TILE_BYTES, tm, 0, c1, row, bar_full + slot * 8, pol);
                if (pos >= pos_t)
                    tma_3d(sb + SM_RING + slot * TILE_BYTES + PIECE_BYTES, tm, 0, c1, row + 48,
                           pos >= pos_t + 6 ? bar + BAR_HALF + (pos - pos_t - 6) * 8 : bar_full + slot * 8, pol);
                deadline += step;
                if (pos == pos_late) step = step * prm.late >> 12;
                if (pos == pos_t - GATE_EARLY) mbar_arrive(bar + BAR_GO);
                if (pos == pos_t + GATE_LATE) mbar_arrive(bar + BAR_GO + 8);
            }
        }
        return;
    }

    if (warp > N_CONS_WARPS + 2 && !owner) return;
    if (tid == N_CONS + 32) {
#pragma unroll
        for (int i = 0; i < N_SLOT; i++) mbar_init(bar_empty + i * 8, RELEASE);
        asm volatile("fence.mbarrier_init.release.cluster;" ::: "memory");
    }
    if (tid == N_CONS + 64) {
#pragma unroll
        for (int i = BAR_GO; i < BAR_READY; i += 8) mbar_init(bar + i, 1);
#pragma unroll
        for (int i = BAR_HALF; i < BAR_READY; i += 8) mbar_expect_tx(bar + i, PIECE_BYTES);
        mbar_expect_tx(bar + BAR_X, D_MODEL * 2 + 4);
        mbar_expect_tx(bar + BAR_Q, (1 + tri) * CL * D_HEAD * 4);
        mbar_expect_tx(bar + BAR_ML, n_heads * CL * 8);
#pragma unroll
        for (int i = BAR_O; i <= BAR_S; i += 8) mbar_expect_tx(bar + i, 1024);
        asm volatile("fence.mbarrier_init.release.cluster;" ::: "memory");
    }
    __syncwarp();
    cluster_arrive();
    float* sst = reinterpret_cast<float*>(sp + SM_ST);
    if (tid < 8) *reinterpret_cast<uint2*>(sp + SM_XN + D_MODEL * 2 + tid * 8) = make_uint2(0u, 0u);
    if (rank == CL - 1 && warp >= V_WARPS && warp < N_CONS_WARPS) {
        if (warp == V_WARPS) {
            const uint32_t ep = ll_ld(g_epoch);
            cluster_wait();
            if (lane < CL) st_async(mapa(sb + SM_EPOCH, lane), __uint_as_float(ep), mapa(bar + BAR_X, lane));
        } else {
            uint2 u[5];
#pragma unroll
            for (int i = 0; i < 5; i++) u[i] = *reinterpret_cast<const uint2*>(prm.x + i * 128 + lane * 4);
            float s = 0.f;
#pragma unroll
            for (int i = 0; i < 5; i++) s += (bf_lo(u[i].x) + bf_hi(u[i].x)) + (bf_lo(u[i].y) + bf_hi(u[i].y));
#pragma unroll
            for (int o = 16; o > 0; o >>= 1) s += __shfl_xor_sync(0xffffffffu, s, o);
            const float mean = s * (1.f / D_MODEL);
            s = 0.f;
#pragma unroll
            for (int i = 0; i < 5; i++) {
                const float a = bf_lo(u[i].x) - mean, b = bf_hi(u[i].x) - mean, c = bf_lo(u[i].y) - mean, d = bf_hi(u[i].y) - mean;
                s += fmaf(a, a, b * b) + fmaf(c, c, d * d);
            }
#pragma unroll
            for (int o = 16; o > 0; o >>= 1) s += __shfl_xor_sync(0xffffffffu, s, o);
            const float mean_b = bf16r(mean);
            float den;
            asm("sqrt.approx.f32 %0, %1;" : "=f"(den) : "f"(bf16r(bf16r(s * (1.f / D_MODEL)) + 1e-5f)));
            const float inv = rcp(bf16r(den));
#pragma unroll
            for (int i = 0; i < 5; i++) {
                const uint32_t d0 = pack_bf16(bf_lo(u[i].x) - mean_b, bf_hi(u[i].x) - mean_b);
                const uint32_t d1 = pack_bf16(bf_lo(u[i].y) - mean_b, bf_hi(u[i].y) - mean_b);
                u[i] = make_uint2(pack_bf16(bf_lo(d0) * inv, bf_hi(d0) * inv), pack_bf16(bf_lo(d1) * inv, bf_hi(d1) * inv));
            }
            cluster_wait();
#pragma unroll 1
            for (int d = 0; d < CL; d++) {
                const uint32_t dst = mapa(sb + SM_XN + lane * 8, d), mb = mapa(bar + BAR_X, d);
#pragma unroll
                for (int i = 0; i < 5; i++) st_async2(dst + i * 256, __uint_as_float(u[i].x), __uint_as_float(u[i].y), mb);
            }
        }
        __syncwarp();
    }
    if (warp == N_CONS_WARPS + 1 ? rank >= V_WARPS : warp > N_CONS_WARPS && !owner) {
        named_arrive(6, n_start);
        return;
    }
    named_sync(6, n_start);
    if (tid == 0) mbar_arrive(bar + BAR_READY);
    mbar_wait(bar + BAR_X, 0);
    const uint32_t epoch = lds32(sb + SM_EPOCH);
    const uint32_t tag = 1u + (epoch & 1u);

    if (warp == N_CONS_WARPS + 1) {
        const bool fin = owner && rank < 4;
        const int col = oc * 64 + rank * 16 + (lane & 1) * 8 + ((lane >> 1) & 7);
        uint16_t* const out = reinterpret_cast<uint16_t*>(prm.out) + col;
        mbar_wait(bar + BAR_ML, 0);
        uint32_t xv = 0;
        if (fin) xv = reinterpret_cast<const uint16_t*>(prm.x)[col];
        float wv;
        {
            const uint32_t ma = sb + SM_ML + (lane < n_heads * CL ? lane : 0) * 8;
            const float mi = lds_f(ma);
            float m = fmaxf(mi, __shfl_xor_sync(0xffffffffu, mi, 1));
            m = fmaxf(m, __shfl_xor_sync(0xffffffffu, m, 2));
            m = fmaxf(m, __shfl_xor_sync(0xffffffffu, m, 4));
            const float ei = ex2((mi - m) * LOG2E);
            float den = ei * lds_f(ma + 4);
            den += __shfl_xor_sync(0xffffffffu, den, 1);
            den += __shfl_xor_sync(0xffffffffu, den, 2);
            den += __shfl_xor_sync(0xffffffffu, den, 4);
            wv = ei * rcp(den);
        }
#pragma unroll 1
        for (int hh = 0; hh < n_heads; hh++) {
            float w[CL];
#pragma unroll
            for (int s = 0; s < CL; s++) w[s] = __shfl_sync(0xffffffffu, wv, hh * CL + s);
            uint32_t* dst = g_x + D_FF + head_at(cl, hh, tri) * D_HEAD + rank * 32 + lane;
            const uint32_t src = sb + SM_OP + hh * 1024 + lane * 4;
            mbar_wait(bar + BAR_O + hh * 8, 0);
            float v[CL];
#pragma unroll
            for (int s = 0; s < CL; s++) v[s] = lds_f(src + s * 128);
            const float o = (fmaf(w[1], v[1], w[0] * v[0]) + fmaf(w[3], v[3], w[2] * v[2])) +
                            (fmaf(w[5], v[5], w[4] * v[4]) + fmaf(w[7], v[7], w[6] * v[6]));
            ll_store(dst, __float_as_uint(bf16r(o)) | tag);
        }
        if (fin) {
            mbar_wait(bar + BAR_G, 0);
            const uint32_t g = pack_bf16(silu_f(bf16r(lds_colsum(sb + SM_FG, lane))), 0.f);
            asm volatile("{\n.reg .pred p;\nsetp.eq.u32 p, %2, 0;\n@p st.relaxed.gpu.global.b32 [%0], %1;\n}" ::"l"(g_epoch), "r"(epoch + 1u), "r"(oc + rank + lane) : "memory");
            mbar_wait(bar + BAR_S, 0);
            uint32_t res = pack_bf16(lds_colsum(sb + SM_FS, lane), 0.f);
            asm("mul.rn.bf16x2 %0, %0, %1;" : "+r"(res) : "r"(g));
            asm("add.rn.bf16x2 %0, %0, %1;" : "+r"(res) : "r"(xv));
            if (lane < 16) *out = (uint16_t)res;
        }
        return;
    }
    if (warp >= N_CONS_WARPS + 2) {
        const int gw = warp - (N_CONS_WARPS + 2);
        mbar_wait(bar + BAR_GO, 0);
#pragma unroll 1
        for (int round = 0; round < 2; round++) {
            const int i0 = round * 4 + 2 + gw;
            const uint32_t* src0 = g_x + tail_row(rank, i0) + lane * 4;
            const uint32_t* src1 = g_x + tail_row(rank, gw) + lane * 4;
            if (round == 1) {
                named_arrive(8, N_CONS + N_GATHER);
                mbar_wait(bar + BAR_GO + 8, 0);
            }
            uint4 v0 = make_uint4(0u, 0u, 0u, 0u), v1 = v0;
            const bool second = round == 0 && gw < 2 && lane < 24;
            uint32_t miss0 = lane < 24, miss1 = second;
            unsigned n = 0;
#pragma unroll 1
            while (true) {
                ll_ld4_if(v0, src0, miss0);
                ll_ld4_if(v1, src1, miss1);
                if (ll_bad4(v0, tag) == 0) miss0 = 0;
                if (ll_bad4(v1, tag) == 0) miss1 = 0;
                if (__all_sync(0xffffffffu, (miss0 | miss1) == 0) || ++n > SPIN_LIMIT) break;
            }
            if (lane < 24)
                *reinterpret_cast<uint2*>(sp + SM_OV + i0 * 192 + lane * 8) = make_uint2(__byte_perm(v0.x, v0.y, 0x7632), __byte_perm(v0.z, v0.w, 0x7632));
            if (second)
                *reinterpret_cast<uint2*>(sp + SM_OV + gw * 192 + lane * 8) = make_uint2(__byte_perm(v1.x, v1.y, 0x7632), __byte_perm(v1.z, v1.w, 0x7632));
        }
        named_arrive(3, N_CONS + N_GATHER);
        return;
    }


    const int q4 = lane & 3, g8 = lane >> 2;
    const int rowT = (lane & 7) + ((lane >> 4) << 3), hiT = (lane >> 3) & 1;
    const uint32_t off_v = ((3 * rowT + (warp >> 1)) * 128 + ((hiT ^ ((3 * rowT + (warp >> 1)) & 7)) << 4)) ^ ((warp & 1) << 6);

    if (warp < V_WARPS) {
#pragma unroll 1
        for (int part = 0; part <= tri; part++) {
            const uint32_t xa = sb + SM_XN + ((part ? rank * 16 - 1280 : (rank & 3) * 16) + 2 * q4) * 2, xs = 128 << part;
            float acc[2][4] = {};
#pragma unroll 1
            for (int p = part * 10; p < 10 + part * 5; p++) {
                const uint32_t b0 = lds32(xa + p * xs), b1 = lds32(xa + p * xs + 16);
                mbar_wait(bar_full + (p >> 1) * 8, 0);
                uint32_t a[4];
                ldsm_x4_t(a, sb + SM_RING + p * PIECE_BYTES + off_v);
                mma_bf16(acc[0], a, b0, b1);
                ldsm_x4_t(a, sb + SM_RING + p * PIECE_BYTES + (off_v ^ 32));
                mma_bf16(acc[1], a, b0, b1);
                __syncwarp();
                if (lane == 0) mbar_arrive_n(bar_empty + (p >> 1) * 8, p == 14 ? RELEASE / V_WARPS : RELEASE / V_WARPS / 2);
            }
            const float v = pick4(acc[0][0], acc[0][2], acc[1][0], acc[1][2], q4);
            const uint32_t dst = sb + SM_QP + ((part * CL + rank) * D_HEAD + warp * 32 + q4 * 8 + g8) * 4;
#pragma unroll
            for (int d = 0; d < CL; d++) st_async(mapa(dst, d), v, mapa(bar + BAR_Q, d));
        }
        mbar_wait(bar + BAR_Q, 0);
        const float* qp = reinterpret_cast<const float*>(sp + SM_QP) + tid;
        __nv_bfloat16* qs = reinterpret_cast<__nv_bfloat16*>(sp + SM_Q) + tid;
        qs[0] = __float2bfloat16_rn((qp[0] + qp[192]) + (qp[384] + qp[576]));
        qs[(tri + 1) * D_HEAD] = __float2bfloat16_rn((qp[768] + qp[960]) + (qp[1152] + qp[1344]));
        if (tri) {
            qp += CL * D_HEAD;
            qs[D_HEAD] = __float2bfloat16_rn(((qp[0] + qp[192]) + (qp[384] + qp[576])) + ((qp[768] + qp[960]) + (qp[1152] + qp[1344])));
        }
    }
    named_sync(1, N_CONS);

    {
        const int rowN = (lane & 7) + (((lane >> 3) & 1) << 3), hiN = lane >> 4;
#pragma unroll 1
        for (int hh = 0; hh < n_heads; hh++) {
            float s0 = 0.f, s1 = 0.f;
#pragma unroll 1
            for (int i = 0; i < 2; i++) {
                const int u = hh * HEAD_TILES + i * 8 + warp, pos = pos_k + u, slot = pos & (N_SLOT - 1);
                mbar_wait(bar_full + slot * 8, (pos >> 4) & 1);
                const uint32_t tb = sb + SM_RING + slot * TILE_BYTES;
                float acc[2][2][4] = {};
#pragma unroll 1
                for (int j = 0; j < 3; j++) {
                    const int swz = u < 2 ? 0 : (3 * rowN + j) & 7;
                    const uint32_t oj = tb + (3 * rowN + j) * 128 + ((hiN ^ swz) << 4);
                    const uint32_t qa = sb + SM_Q + (hh * D_HEAD + j * 64 + 2 * q4) * 2;
#pragma unroll
                    for (int k = 0; k < 4; k++) {
                        const uint32_t b0 = lds32(qa + k * 32), b1 = lds32(qa + k * 32 + 16);
                        uint32_t a[4];
                        ldsm_x4(a, oj ^ (k << 5));
                        mma_bf16(acc[0][k & 1], a, b0, b1);
                        ldsm_x4(a, (oj + PIECE_BYTES) ^ (k << 5));
                        mma_bf16(acc[1][k & 1], a, b0, b1);
                    }
                }
                __syncwarp();
                if (lane == 0) mbar_arrive_n(bar_empty + slot * 8, RELEASE);
                const float raw = pick4(acc[0][0][0] + acc[0][1][0], acc[0][0][2] + acc[0][1][2],
                                        acc[1][0][0] + acc[1][1][0], acc[1][0][2] + acc[1][1][2], q4);
                s0 = s1;
                s1 = bf16r(bf16r(raw) * 0.07216878364870323f);
            }
            float m = fmaxf(s0, s1);
#pragma unroll
            for (int o = 16; o > 0; o >>= 1) m = fmaxf(m, __shfl_xor_sync(0xffffffffu, m, o));
            if (lane == 0) sst[hh * 8 + warp] = m;
            named_sync(1, N_CONS);
#pragma unroll
            for (int w = 0; w < 8; w++) m = fmaxf(m, sst[hh * 8 + w]);
            const float p0 = ex2((s0 - m) * LOG2E), p1 = ex2((s1 - m) * LOG2E);
            float l = p0 + p1;
#pragma unroll
            for (int o = 16; o > 0; o >>= 1) l += __shfl_xor_sync(0xffffffffu, l, o);
            if (lane == 0) sst[24 + hh * 8 + warp] = l;
            __nv_bfloat16* ps = reinterpret_cast<__nv_bfloat16*>(sp + SM_P) + hh * 512 + warp * 32 + q4 * 8 + g8;
            ps[0] = __float2bfloat16_rn(p0);
            ps[256] = __float2bfloat16_rn(p1);
        }
        named_sync(1, N_CONS);
        if (warp == 7 && lane < n_heads * CL && (lane & 7) < V_WARPS) {
            const float* st = sst + (lane & 24);
            float m = st[0], l = st[24];
#pragma unroll
            for (int w = 1; w < 8; w++) { m = fmaxf(m, st[w]); l += st[24 + w]; }
            st_async2(mapa(sb + SM_ML + ((lane & 24) + rank) * 8, lane & 7), m, l, mapa(bar + BAR_ML, lane & 7));
        }
    }

    const uint32_t off_w = (warp >> 2) * PIECE_BYTES + rowT * 128 + (((((warp & 3) << 1) | hiT) ^ (rowT & 7)) << 4);

    if (ffn) {
#pragma unroll 1
        for (int res = 0; res < 2; res++) {
            float acc[3][4] = {};
#pragma unroll 1
            for (int i = 0; i < W_TILES / 2; i++) {
                const int pos = pos_w + res * (W_TILES / 2) + i, slot = pos & (N_SLOT - 1);
                const uint32_t xa = sb + SM_XN + (i * 96 + (warp >> 2) * 48 + 2 * q4) * 2;
                mbar_wait(bar_full + slot * 8, (pos >> 4) & 1);
#pragma unroll
                for (int k = 0; k < 3; k++) {
                    uint32_t a[4];
                    ldsm_x4_t(a, sb + SM_RING + slot * TILE_BYTES + off_w + k * 2048);
                    mma_bf16(acc[k], a, lds32(xa + k * 32), lds32(xa + k * 32 + 16));
                }
                __syncwarp();
                if (lane == 0) mbar_arrive_n(bar_empty + slot * 8, RELEASE / N_CONS_WARPS);
            }
            if (q4 < 2)
                reinterpret_cast<float*>(sp + SM_FG)[res * 128 + warp * 16 + q4 * 8 + g8] =
                    q4 ? (acc[0][2] + acc[1][2]) + acc[2][2] : (acc[0][0] + acc[1][0]) + acc[2][0];
        }
        named_sync(1, N_CONS);
        if (warp >= V_WARPS) {
            const float* f = reinterpret_cast<const float*>(sp + SM_FG) + (tid & 63);
            const float h = bf16r(bf16r(silu_f(bf16r(f[0] + f[64]))) * bf16r(f[128] + f[192]));
            ll_store(g_x + (cta - CL_FFN * CL) * 64 + (tid & 63), __float_as_uint(h) | tag);
        }
    }

    if (warp < V_WARPS) {
        const uint32_t rdst = mapa(sb + SM_OP + rank * 128 + (q4 * 8 + g8) * 4, warp), rbar = mapa(bar + BAR_O, warp);
#pragma unroll 1
        for (int hh = 0; hh < n_heads; hh++) {
            float oacc[2][2][4] = {};
#pragma unroll 2
            for (int u = hh * HEAD_TILES; u < (hh + 1) * HEAD_TILES; u++) {
                const int pos = pos_v + u, slot = pos & (N_SLOT - 1);
                uint32_t ta = sb + SM_RING + slot * TILE_BYTES + off_v, tc = ta ^ 32;
                asm volatile("" : "+r"(ta), "+r"(tc));
                const uint32_t pa = sb + SM_P + (u * 32 + 2 * q4) * 2;
                const uint32_t b0 = lds32(pa), b1 = lds32(pa + 16), b2 = lds32(pa + 32), b3 = lds32(pa + 48);
                mbar_wait(bar_full + slot * 8, (pos >> 4) & 1);
                uint32_t a[4][4];
                ldsm_x4_t(a[0], ta);
                ldsm_x4_t(a[1], tc);
                ldsm_x4_t(a[2], ta + PIECE_BYTES);
                ldsm_x4_t(a[3], tc + PIECE_BYTES);
                mma_bf16(oacc[0][0], a[0], b0, b1);
                mma_bf16(oacc[1][0], a[1], b0, b1);
                mma_bf16(oacc[0][1], a[2], b2, b3);
                mma_bf16(oacc[1][1], a[3], b2, b3);
                __syncwarp();
                if (lane == 0) mbar_arrive_n(bar_empty + slot * 8, RELEASE / V_WARPS);
            }
            const float v = pick4(oacc[0][0][0] + oacc[0][1][0], oacc[0][0][2] + oacc[0][1][2],
                                  oacc[1][0][0] + oacc[1][1][0], oacc[1][0][2] + oacc[1][1][2], q4);
            st_async(rdst + hh * 1024, v, rbar + hh * 8);
        }
    }
    if (!owner) return;

    {
        constexpr int P0 = POS_K2 + 4 * HEAD_TILES;
        const uint32_t rdst = mapa(sb + SM_FG + (rank * 2 + (warp >> 2)) * 64 + g8 * 8, warp & 3);
        const uint32_t rbar = mapa(bar + BAR_G, warp & 3);
        const uint32_t va = sb + SM_OV + ((warp >> 2) * 48 + 2 * q4) * 2, tw = sb + SM_RING + off_w;
        named_sync(8, N_CONS + N_GATHER);
        auto send = [&](const float (&acc)[3][4], uint32_t dst, uint32_t mb) {
            if (q4 == 0) st_async2(dst, (acc[0][0] + acc[1][0]) + acc[2][0], (acc[0][2] + acc[1][2]) + acc[2][2], mb);
        };
        float acc[3][4] = {};
#pragma unroll 1
        for (int i = 0; i < 6; i++) {
            const int slot = (P0 + i) & (N_SLOT - 1);
            uint32_t b[3][2];
#pragma unroll
            for (int k = 0; k < 3; k++) { b[k][0] = lds32(va + i * 192 + k * 32); b[k][1] = lds32(va + i * 192 + k * 32 + 16); }
            mbar_wait(bar_full + slot * 8, ((P0 + i) >> 4) & 1);
#pragma unroll
            for (int k = 0; k < 3; k++) {
                uint32_t a[4];
                ldsm_x4_t(a, tw + slot * TILE_BYTES + k * 2048);
                mma_bf16(acc[k], a, b[k][0], b[k][1]);
            }
            if (i == 1) {
                send(acc, rdst, rbar);
#pragma unroll
                for (int k = 0; k < 3; k++) acc[k][0] = acc[k][1] = acc[k][2] = acc[k][3] = 0.f;
            }
        }
        static_assert(((P0 + 6) >> 4) % 2 == 0 && (P0 + 9) >> 4 == (P0 + 6) >> 4, "both kinds of barrier complete a phase of parity 0");
        const uint32_t hb = warp < 4 ? bar_full + ((P0 + 6) & (N_SLOT - 1)) * 8 : bar + BAR_HALF;
        uint32_t a[4][3][4], b[4][3][2];
        named_sync(3, N_CONS + N_GATHER);
#pragma unroll
        for (int i = 0; i < 4; i++)
#pragma unroll
            for (int k = 0; k < 3; k++) { b[i][k][0] = lds32(va + (6 + i) * 192 + k * 32); b[i][k][1] = lds32(va + (6 + i) * 192 + k * 32 + 16); }
#pragma unroll
        for (int i = 0; i <= 4; i++) {
            if (i < 4) {
                const int slot = (P0 + 6 + i) & (N_SLOT - 1);
                mbar_wait(hb + i * 8, 0);
#pragma unroll
                for (int k = 0; k < 3; k++) ldsm_x4_t(a[i][k], tw + slot * TILE_BYTES + k * 2048);
            }
            if (i >= 1) {
#pragma unroll
                for (int k = 0; k < 3; k++) mma_bf16(acc[k], a[i - 1][k], b[i - 1][k][0], b[i - 1][k][1]);
            }
        }
        send(acc, rdst + (SM_FS - SM_FG), rbar + (BAR_S - BAR_G));
    }
}

typedef CUresult (*EncodeTiledFn)(CUtensorMap*, CUtensorMapDataType, cuuint32_t, void*, const cuuint64_t*,
                                  const cuuint64_t*, const cuuint32_t*, const cuuint32_t*, CUtensorMapInterleave,
                                  CUtensorMapSwizzle, CUtensorMapL2promotion, CUtensorMapFloatOOBfill);

void encode_map(EncodeTiledFn fn, CUtensorMap* m, const void* base, cuuint64_t rows, cuuint64_t cols, cuuint32_t b1, cuuint32_t b2) {
    const cuuint64_t dims[3] = {64, cols / 64, rows};
    const cuuint64_t strides[2] = {128, cols * 2};
    const cuuint32_t box[3] = {64, b1, b2};
    const cuuint32_t estr[3] = {1, 1, 1};
    fn(m, CU_TENSOR_MAP_DATA_TYPE_BFLOAT16, 3, const_cast<void*>(base), dims, strides, box, estr,
       CU_TENSOR_MAP_INTERLEAVE_NONE, CU_TENSOR_MAP_SWIZZLE_128B, CU_TENSOR_MAP_L2_PROMOTION_NONE,
       CU_TENSOR_MAP_FLOAT_OOB_FILL_NONE);
}

}

extern "C" void kernel_launch(void* const* d_in, const int* in_sizes, int n_in, void* d_out, int out_size) {
    (void)in_sizes; (void)n_in; (void)out_size;
    static EncodeTiledFn encode = nullptr;
    static double pace_scale = 1.0;
    static void* scratch = nullptr;
    if (!encode) {
        int dev = 0, mem_khz = 0, bus_bits = 0;
        cudaGetDevice(&dev);
        cudaDeviceGetAttribute(&mem_khz, cudaDevAttrMemoryClockRate, dev);
        cudaDeviceGetAttribute(&bus_bits, cudaDevAttrGlobalMemoryBusWidth, dev);
        const double peak_gbs = 2.0 * mem_khz * 1e-6 * bus_bits / 8.0;
        if (peak_gbs > 0.0) pace_scale = PACE_REF_GBS / peak_gbs;
        void* fn = nullptr;
        cudaDriverEntryPointQueryResult qr;
        cudaGetDriverEntryPoint("cuTensorMapEncodeTiled", &fn, cudaEnableDefault, &qr);
        encode = reinterpret_cast<EncodeTiledFn>(fn);
        cudaFuncSetAttribute(fused_decode_kernel, cudaFuncAttributeMaxDynamicSharedMemorySize, SM_ALLOC);
        cudaGetSymbolAddress(&scratch, g_scratch);
    }
    CUtensorMap tm_k, tm_v, tm_wq, tm_w1, tm_w3, tm_wo, tm_w2;
    encode_map(encode, &tm_k, d_in[1], (cuuint64_t)N_HEAD * SEQ, D_HEAD, 3, 32);
    encode_map(encode, &tm_v, d_in[2], (cuuint64_t)N_HEAD * SEQ, D_HEAD, 3, 32);
    encode_map(encode, &tm_wq, d_in[3], D_MODEL, N_HEAD * D_HEAD, 3, 16);
    encode_map(encode, &tm_w1, d_in[6], D_MODEL, D_FF, 1, 96);
    encode_map(encode, &tm_w3, d_in[7], D_MODEL, D_FF, 1, 96);
    encode_map(encode, &tm_wo, d_in[4], N_HEAD * D_HEAD, D_MODEL, 1, 48);
    encode_map(encode, &tm_w2, d_in[8], D_FF, D_MODEL, 1, 48);
    Params prm;
    prm.x = static_cast<const __nv_bfloat16*>(d_in[0]);
    prm.out = static_cast<__nv_bfloat16*>(d_out);
    prm.k = static_cast<const __nv_bfloat16*>(d_in[1]) + (size_t)(SEQ - WIN) * D_HEAD;
    prm.scratch = static_cast<uint32_t*>(scratch);
    auto step = [&](double pace, double bytes, int pieces) { return (uint16_t)(8.0 * pace * pace_scale * bytes / (128.0 * TILE_BYTES) / pieces); };
    const double b_wq = 2.0 * D_MODEL * N_HEAD * D_HEAD;
    const double b_mid = 4.0 * N_HEAD * WIN * D_HEAD - 2.0 * N_CTA * TILE_BYTES + 4.0 * D_MODEL * D_FF;
    const double b_tail = 2.0 * D_MODEL * (D_FF + N_HEAD * D_HEAD);
    prm.step_wq2 = step(PACE_HEAD, b_wq, 10);
    prm.step_wq3 = step(PACE_HEAD, b_wq, 15);
    prm.step_own = step(PACE_MID, b_mid, 4 * HEAD_TILES - 2);
    prm.step_ffn = step(PACE_MID, b_mid, 4 * HEAD_TILES - 2 + W_TILES);
    prm.step_tri = step(PACE_MID, b_mid, 6 * HEAD_TILES - 2);
    prm.step_tail = step(PACE_TAIL, b_tail, TAIL_TILES);
    prm.late = (uint16_t)(4096.0 * PACE_LATE / PACE_MID + 0.5);
    prm.pad = 0;
    fused_decode_kernel<<<N_CTA, N_THREADS, SM_ALLOC, cudaStreamPerThread>>>(prm, tm_wq, tm_w1, tm_w3, tm_k, tm_v, tm_wo, tm_w2);
}
```

```cpp
#include <cuda_runtime.h>
#include <cuda_bf16.h>
#include <cuda.h>
#include <stdint.h>

namespace {

constexpr int D_MODEL = 640;
constexpr int N_HEAD = 32;
constexpr int D_HEAD = 192;
constexpr int SEQ = 32768;
constexpr int WIN = 4096;
constexpr int D_FF = 1536;

constexpr int CL = 8;
constexpr int N_CL = 15;
constexpr int N_CTA = CL * N_CL;
constexpr int CL_FFN = 1, CL_TRI = CL_FFN + 3, CL_OWN = CL_TRI + 2;
constexpr int TILE_BYTES = 12288;
constexpr int PIECE_BYTES = TILE_BYTES / 2;
constexpr int N_SLOT = 16;
constexpr int HEAD_TILES = WIN / CL / 32;
constexpr int W_TILES = 14;
constexpr int TAIL_TILES = 10;
constexpr int POS_K2 = 5, POS_K3 = 8;
constexpr int POS_T = POS_K2 + 4 * HEAD_TILES, SLOT_T = POS_T % N_SLOT;
static_assert(SLOT_T + TAIL_TILES <= N_SLOT && (POS_T / N_SLOT) % 2 == 0, "the tail uses consecutive slots in a phase of parity 0");

constexpr int N_CONS_WARPS = 8;
constexpr int N_CONS = N_CONS_WARPS * 32;
constexpr int N_GATHER = 128;
constexpr int N_THREADS = N_CONS + 64 + N_GATHER;
constexpr int V_WARPS = 6;
constexpr int RELEASE = 24;

constexpr double PACE_HEAD = 490, PACE_MID = 479, PACE_LATE = 495, PACE_TAIL = 484, PACE_REF_GBS = 3352.32;
constexpr int START_DELAY = 140;
constexpr int WINDOW_OWN = 5, WINDOW_FFN = 6, WINDOW_TRI = 8;
constexpr int SLIP = 50;
constexpr int GATE_EARLY = 4, GATE_LATE = 7;

constexpr unsigned SPIN_LIMIT = 1u << 22;

constexpr int SM_RING = 0;
constexpr int SM_BAR = N_SLOT * TILE_BYTES;
constexpr int BAR_FULL = 0, BAR_EMPTY = 128, BAR_GO = 256, BAR_Q = 272, BAR_ML = 280, BAR_O = 288, BAR_G = 312, BAR_S = 320, BAR_X = 328,
              BAR_HALF = 336, BAR_READY = 368;
constexpr int SM_T0 = SM_BAR + 448, SM_EPOCH = SM_BAR + 452;
constexpr int SM_XN = SM_BAR + 512;
constexpr int SM_Q = SM_XN + 1408;
constexpr int SM_ST = SM_Q + 1152;
constexpr int SM_ML = SM_ST + 256;
constexpr int SM_P = SM_ML + 256;
constexpr int SM_QP = SM_P + 3072;
constexpr int SM_OP = SM_QP + 12288;
constexpr int SM_OV = SM_OP + 3072;
constexpr int SM_FG = SM_OV + 1920;
constexpr int SM_FS = SM_FG + 1024;
constexpr int SM_ALLOC = SM_FS + 1024 + 1024;

constexpr int XO_H = 32;
constexpr int XO_END = XO_H + D_FF + N_HEAD * D_HEAD;
__device__ __align__(128) uint32_t g_scratch[XO_END];

__device__ __forceinline__ uint32_t smem_u32(const void* p) { return (uint32_t)__cvta_generic_to_shared(p); }

__device__ __forceinline__ void mbar_init(uint32_t bar, uint32_t cnt) {
    asm volatile("mbarrier.init.shared::cta.b64 [%0], %1;" ::"r"(bar), "r"(cnt) : "memory");
}
__device__ __forceinline__ void mbar_expect_tx(uint32_t bar, uint32_t bytes) {
    asm volatile("mbarrier.arrive.expect_tx.shared::cta.b64 _, [%0], %1;" ::"r"(bar), "r"(bytes) : "memory");
}
__device__ __forceinline__ void mbar_arrive(uint32_t bar) {
    asm volatile("mbarrier.arrive.shared::cta.b64 _, [%0];" ::"r"(bar) : "memory");
}
__device__ __forceinline__ void mbar_wait(uint32_t bar, uint32_t parity) {
    asm volatile(
        "{\n.reg .pred p, q;\n.reg .u32 n;\n"
        "mov.u32 n, 0;\n"
        "WAIT_LOOP:\n"
        "add.u32 n, n, 1;\n"
        "setp.lt.u32 q, n, %2;\n"
        "mbarrier.try_wait.parity.shared::cta.b64 p, [%0], %1;\n"
        "and.pred q, q, !p;\n"
        "@q bra WAIT_LOOP;\n}"
        ::"r"(bar), "r"(parity), "n"(SPIN_LIMIT) : "memory");
}
__device__ __forceinline__ void named_sync(int id, int n) {
    asm volatile("bar.sync %0, %1;" ::"r"(id), "r"(n) : "memory");
}
__device__ __forceinline__ void named_arrive(int id, int n) {
    asm volatile("bar.arrive %0, %1;" ::"r"(id), "r"(n) : "memory");
}
__device__ __forceinline__ uint64_t stream_policy() {
    uint64_t pol;
    asm volatile("createpolicy.fractional.L2::evict_first.b64 %0, 1.0;" : "=l"(pol));
    return pol;
}
__device__ __forceinline__ void bulk_load(uint32_t dst, const void* src, uint32_t bytes, uint32_t bar, uint64_t pol) {
    asm volatile("cp.async.bulk.shared::cluster.global.mbarrier::complete_tx::bytes.L2::cache_hint [%0], [%1], %2, [%3], %4;"
                 ::"r"(dst), "l"(src), "r"(bytes), "r"(bar), "l"(pol) : "memory");
}
__device__ __forceinline__ void tma_3d(uint32_t dst, const CUtensorMap* tm, int c0, int c1, int c2, uint32_t bar, uint64_t pol) {
    asm volatile("cp.async.bulk.tensor.3d.shared::cluster.global.mbarrier::complete_tx::bytes.L2::cache_hint [%0], [%1, {%3, %4, %5}], [%2], %6;"
                 ::"r"(dst), "l"(tm), "r"(bar), "r"(c0), "r"(c1), "r"(c2), "l"(pol) : "memory");
}
__device__ __forceinline__ void prefetch_tmap(const CUtensorMap* tm) {
    asm volatile("prefetch.tensormap [%0];" ::"l"(tm) : "memory");
}
__device__ __forceinline__ void ldsm_x4(uint32_t (&r)[4], uint32_t addr) {
    asm volatile("ldmatrix.sync.aligned.m8n8.x4.shared.b16 {%0,%1,%2,%3}, [%4];"
                 : "=r"(r[0]), "=r"(r[1]), "=r"(r[2]), "=r"(r[3]) : "r"(addr) : "memory");
}
__device__ __forceinline__ void ldsm_x4_t(uint32_t (&r)[4], uint32_t addr) {
    asm volatile("ldmatrix.sync.aligned.m8n8.x4.trans.shared.b16 {%0,%1,%2,%3}, [%4];"
                 : "=r"(r[0]), "=r"(r[1]), "=r"(r[2]), "=r"(r[3]) : "r"(addr) : "memory");
}
__device__ __forceinline__ void mma_bf16(float (&c)[4], const uint32_t (&a)[4], uint32_t b0, uint32_t b1) {
    asm volatile("mma.sync.aligned.m16n8k16.row.col.f32.bf16.bf16.f32 {%0,%1,%2,%3}, {%4,%5,%6,%7}, {%8,%9}, {%0,%1,%2,%3};"
                 : "+f"(c[0]), "+f"(c[1]), "+f"(c[2]), "+f"(c[3])
                 : "r"(a[0]), "r"(a[1]), "r"(a[2]), "r"(a[3]), "r"(b0), "r"(b1));
}
__device__ __forceinline__ float bf16r(float v) {
    uint32_t p;
    asm("cvt.rn.bf16x2.f32 %0, %1, %2;" : "=r"(p) : "f"(v), "f"(0.f));
    return __uint_as_float(p);
}
__device__ __forceinline__ uint32_t lds32(uint32_t addr) {
    uint32_t v;
    asm volatile("ld.shared.b32 %0, [%1];" : "=r"(v) : "r"(addr) : "memory");
    return v;
}
__device__ __forceinline__ float bf_lo(uint32_t v) { return __uint_as_float(v << 16); }
__device__ __forceinline__ float bf_hi(uint32_t v) { return __uint_as_float(v & 0xffff0000u); }
__device__ __forceinline__ uint32_t pack_bf16(float lo, float hi) {
    const __nv_bfloat162 p = __floats2bfloat162_rn(lo, hi);
    return *reinterpret_cast<const uint32_t*>(&p);
}
__device__ __forceinline__ uint32_t now_ns() {
    unsigned long long t;
    asm volatile("mov.u64 %0, %%globaltimer;" : "=l"(t));
    return (uint32_t)t;
}

__device__ __forceinline__ void wait_until(uint32_t t_start, uint32_t deadline) {
    unsigned n = 0;
    while (now_ns() - t_start < deadline && ++n < SPIN_LIMIT) {}
}

__device__ __forceinline__ uint32_t ll_bad4(const uint4& v, uint32_t tag) {
    uint32_t lo, hi;
    asm("lop3.b32 %0, %1, %2, %3, 0x7E;" : "=r"(lo) : "r"(v.x), "r"(v.y), "r"(tag));
    asm("lop3.b32 %0, %1, %2, %3, 0x7E;" : "=r"(hi) : "r"(v.z), "r"(v.w), "r"(tag));
    return (lo | hi) & 3u;
}
__device__ __forceinline__ float ex2(float v) {
    float r;
    asm("ex2.approx.ftz.f32 %0, %1;" : "=f"(r) : "f"(v));
    return r;
}
__device__ __forceinline__ float rcp(float v) {
    float r;
    asm("rcp.approx.ftz.f32 %0, %1;" : "=f"(r) : "f"(v));
    return r;
}
constexpr float LOG2E = 1.4426950408889634f;
__device__ __forceinline__ void ll_store(uint32_t* p, uint32_t w) {
    asm volatile("st.relaxed.gpu.global.b32 [%0], %1;" ::"l"(p), "r"(w) : "memory");
}
__device__ __forceinline__ uint32_t ll_ld(const uint32_t* p) {
    uint32_t v;
    asm volatile("ld.relaxed.gpu.global.b32 %0, [%1];" : "=r"(v) : "l"(p) : "memory");
    return v;
}
__device__ __forceinline__ float pick4(float a, float b, float c, float d, int j) {
    const float lo = (j & 1) ? b : a, hi = (j & 1) ? d : c;
    return (j & 2) ? hi : lo;
}
__device__ __forceinline__ float silu_f(float v) { return v * rcp(1.f + ex2(-LOG2E * v)); }

__device__ __forceinline__ void mbar_arrive_n(uint32_t bar, uint32_t n) {
    asm volatile("mbarrier.arrive.shared::cta.b64 _, [%0], %1;" ::"r"(bar), "r"(n) : "memory");
}
__device__ __forceinline__ uint32_t mapa(uint32_t addr, uint32_t rank) {
    uint32_t d;
    asm("mapa.shared::cluster.u32 %0, %1, %2;" : "=r"(d) : "r"(addr), "r"(rank));
    return d;
}
__device__ __forceinline__ void st_async(uint32_t dst, float v, uint32_t bar) {
    asm volatile("st.async.weak.shared::cluster.mbarrier::complete_tx::bytes.f32 [%0], %1, [%2];" ::"r"(dst), "f"(v), "r"(bar) : "memory");
}
__device__ __forceinline__ void st_async2(uint32_t dst, float a, float b, uint32_t bar) {
    asm volatile("st.async.weak.shared::cluster.mbarrier::complete_tx::bytes.v2.f32 [%0], {%1, %2}, [%3];" ::"r"(dst), "f"(a), "f"(b), "r"(bar) : "memory");
}
__device__ __forceinline__ void cluster_arrive() { asm volatile("barrier.cluster.arrive.relaxed.aligned;" ::: "memory"); }
__device__ __forceinline__ void cluster_wait() { asm volatile("barrier.cluster.wait.aligned;" ::: "memory"); }
__device__ __forceinline__ void ll_ld4_if(uint4& v, const uint32_t* p, uint32_t cond) {
    asm volatile("{\n.reg .pred p;\nsetp.ne.u32 p, %5, 0;\n@p ld.relaxed.gpu.global.v4.b32 {%0,%1,%2,%3}, [%4];\n}"
                 : "+r"(v.x), "+r"(v.y), "+r"(v.z), "+r"(v.w) : "l"(p), "r"(cond) : "memory");
}
__device__ __forceinline__ float lds_f(uint32_t addr) { return __uint_as_float(lds32(addr)); }
__device__ __forceinline__ float lds_colsum(uint32_t base, int lane) {
    const uint32_t addr = base + ((lane >> 3) ^ ((lane >> 2) & 1)) * 64 + (lane & 3) * 16;
    uint32_t v[4][4];
#pragma unroll
    for (int i = 0; i < 4; i++) ldsm_x4(v[i], addr + i * 256);
    float t[4];
#pragma unroll
    for (int i = 0; i < 4; i++)
        t[i] = (__uint_as_float(v[i][0]) + __uint_as_float(v[i][1])) + (__uint_as_float(v[i][2]) + __uint_as_float(v[i][3]));
    return ((t[0] + t[1]) + t[2]) + t[3];
}

constexpr uint32_t FIRST_MUL = 257, FIRST_MASK = 0x7807;
__device__ __forceinline__ int pair_head(int cl, int j) { return 2 * cl + j; }
__device__ __forceinline__ int third_head(int cl) { return 2 * N_CL + cl - CL_TRI; }
__device__ __forceinline__ int head_at(int cl, int hh, int tri) { return (hh & tri) ? third_head(cl) : pair_head(cl, hh >> tri); }
__device__ __forceinline__ int tail_row(int rank, int i) {
    if (i < 2) return i * 768 + rank * 96;
    const int j = 4 * (i - 2) + (rank >> 1), q = rank & 1;
    return D_FF + (2 * (j & 15) + (j >> 4)) * D_HEAD + q * 96;
}

struct Params {
    const __nv_bfloat16* x;
    __nv_bfloat16* out;
    const __nv_bfloat16* k;
    uint32_t* scratch;
    uint16_t step_wq2, step_wq3, step_own, step_ffn, step_tri, step_tail, late, pad;
};
static_assert(sizeof(Params) == 48, "Params must fill the rest of the first parameter line");

__global__ void __cluster_dims__(CL, 1, 1) __launch_bounds__(N_THREADS, 1)
fused_decode_kernel(const Params prm, const __grid_constant__ CUtensorMap tm_wq, const __grid_constant__ CUtensorMap tm_w1,
                    const __grid_constant__ CUtensorMap tm_w3, const __grid_constant__ CUtensorMap tm_k,
                    const __grid_constant__ CUtensorMap tm_v, const __grid_constant__ CUtensorMap tm_wo,
                    const __grid_constant__ CUtensorMap tm_w2) {
    extern __shared__ uint8_t smem_raw[];
    asm volatile("{\n.reg .pred p;\nsetp.lt.u32 p, %1, %2;\n@p prefetch.global.L2 [%0];\n}"
                 ::"l"(reinterpret_cast<const char*>(prm.k) + (size_t)(((blockIdx.x * FIRST_MUL) & FIRST_MASK) * (TILE_BYTES / 32) + threadIdx.x) * 32),
                   "r"(threadIdx.x), "n"(TILE_BYTES / 32) : "memory");
    const uint32_t sb = (smem_u32(smem_raw) + 1023u) & ~1023u;
    uint8_t* sp = smem_raw + (sb - smem_u32(smem_raw));
    const uint32_t bar = sb + SM_BAR;
    const uint32_t bar_full = bar + BAR_FULL, bar_empty = bar + BAR_EMPTY;

    const int tid = threadIdx.x;
    const int cta = blockIdx.x, cl = blockIdx.x / CL, rank = blockIdx.x % CL;
    const int tri = cl >= CL_TRI && cl < CL_OWN;
    const int pos_k = tri ? POS_K3 : POS_K2;
    volatile uint32_t* t_first = reinterpret_cast<volatile uint32_t*>(sp + SM_T0);
    if (tid == N_CONS) {
        const __nv_bfloat16* k0 = prm.k + (uint32_t)(pair_head(cl, 0) * SEQ + rank * 32) * (size_t)D_HEAD;
#pragma unroll
        for (int u = 1; u >= 0; u--) {
            const uint32_t fb = bar_full + (pos_k + u) * 8;
            mbar_init(fb, 1);
            asm volatile("fence.mbarrier_init.release.cluster;" ::: "memory");
            mbar_expect_tx(fb, TILE_BYTES);
            bulk_load(sb + SM_RING + (pos_k + u) * TILE_BYTES, k0 + u * (CL * 32 * D_HEAD), TILE_BYTES, fb, stream_policy());
            if (u == 1) *t_first = now_ns();
        }
    }
    if (tid == N_CONS + 32) prefetch_tmap(&tm_wq);
    const int warp = __shfl_sync(0xffffffffu, tid >> 5, 0), lane = tid & 31;
    const bool owner = cl < CL_FFN || cl >= CL_OWN, ffn = !owner && !tri;
    const int oc = cl < CL_FFN ? cl : cl - (CL_OWN - CL_FFN);
    const int n_heads = 2 + tri;
    const int pos_w = pos_k + n_heads * HEAD_TILES;
    const int pos_v = pos_w + (ffn ? W_TILES : 0);
    const int pos_t = pos_v + n_heads * HEAD_TILES;
    uint32_t* const g_epoch = prm.scratch;
    uint32_t* const g_x = prm.scratch + XO_H;
    const int n_start = owner ? N_THREADS : N_THREADS - 96;

    if (warp == N_CONS_WARPS) {
        if (lane == 0) {
#pragma unroll
            for (int i = 2; i < N_SLOT; i++) mbar_init(bar_full + ((pos_k + i) & (N_SLOT - 1)) * 8, 1);
            mbar_init(bar + BAR_READY, 1);
            asm volatile("fence.mbarrier_init.release.cluster;" ::: "memory");
        }
        __syncwarp();
        named_arrive(6, n_start);
        cluster_arrive();
        if (lane == 0) {
            const uint64_t pol = stream_policy();
            const uint32_t t_start = *t_first;
            uint32_t deadline = START_DELAY * 8;
            {
                const uint32_t step = tri ? prm.step_wq3 : prm.step_wq2;
#pragma unroll 1
                for (int p = 0; p < 10 + 5 * tri; p++) {
                    const uint32_t fb = bar_full + (p >> 1) * 8;
                    if (!(p & 1)) mbar_expect_tx(fb, p == 14 ? PIECE_BYTES : TILE_BYTES);
                    const int h = p < 10 ? pair_head(cl, rank >> 2) : third_head(cl);
                    const int row = p < 10 ? p * 64 + (rank & 3) * 16 : (p - 10) * 128 + rank * 16;
                    wait_until(t_start, deadline >> 3);
                    tma_3d(sb + SM_RING + p * PIECE_BYTES, &tm_wq, 0, h * 3, row, fb, pol);
                    deadline += step;
                }
            }
            mbar_wait(bar + BAR_READY, 0);
            uint32_t step = owner ? prm.step_own : (tri ? prm.step_tri : prm.step_ffn);
            const int window = owner ? WINDOW_OWN : (tri ? WINDOW_TRI : WINDOW_FFN);
            const int pos_late = pos_t - (owner ? 16 : (tri ? 24 : 20));
#pragma unroll 1
            for (int pos = pos_k + 2;; pos++) {
                if (pos >= pos_k + 2 + window) mbar_wait(bar_full + ((pos - window) & (N_SLOT - 1)) * 8, ((pos - window) >> 4) & 1);
                deadline = max(deadline, (now_ns() - t_start - SLIP) << 3);
                if (pos == pos_t) break;
                const int slot = pos & (N_SLOT - 1);
                const CUtensorMap* tm;
                int c1 = 0, row;
                if (pos >= pos_w && pos < pos_v) {
                    const bool up = pos >= pos_w + W_TILES / 2;
                    tm = up ? &tm_w3 : &tm_w1;
                    c1 = cta - CL_FFN * CL;
                    row = (pos - pos_w - (up ? W_TILES / 2 : 0)) * 96;
                } else {
                    const int u = pos - (pos < pos_w ? pos_k : pos_v), hh = u >> 4;
                    tm = pos < pos_w ? &tm_k : &tm_v;
                    row = head_at(cl, hh, tri) * SEQ + (SEQ - WIN) + rank * 32 + (u & 15) * (CL * 32);
                }
                if (pos >= N_SLOT) mbar_wait(bar_empty + slot * 8, ((pos >> 4) - 1) & 1);
                mbar_expect_tx(bar_full + slot * 8, TILE_BYTES);
                wait_until(t_start, deadline >> 3);
                tma_3d(sb + SM_RING + slot * TILE_BYTES, tm, 0, c1, row, bar_full + slot * 8, pol);
                deadline += step;
                if (pos == pos_late) step = step * prm.late >> 12;
                if (pos == pos_t - GATE_EARLY) mbar_arrive(bar + BAR_GO);
            }
            if (owner) {
                mbar_wait(bar_empty + (SLOT_T + TAIL_TILES - 1) * 8, ((POS_T >> 4) - 1) & 1);
#pragma unroll
                for (int i = 0; i < TAIL_TILES; i++) mbar_expect_tx(bar_full + (SLOT_T + i) * 8, i < 6 ? TILE_BYTES : PIECE_BYTES);
#pragma unroll 1
                for (int i = 0; i < TAIL_TILES; i++) {
                    const CUtensorMap* tm = i < 2 ? &tm_w2 : &tm_wo;
                    const int row = tail_row(rank, i) - (i < 2 ? 0 : D_FF);
                    const uint32_t dst = sb + SM_RING + (SLOT_T + i) * TILE_BYTES, fb = bar_full + (SLOT_T + i) * 8;
                    wait_until(t_start, deadline >> 3);
                    tma_3d(dst, tm, 0, oc, row, fb, pol);
                    tma_3d(dst + PIECE_BYTES, tm, 0, oc, row + 48, i < 6 ? fb : bar + BAR_HALF + (i - 6) * 8, pol);
                    deadline += prm.step_tail;
                    if (i == GATE_LATE) mbar_arrive(bar + BAR_GO + 8);
                }
            }
        }
        return;
    }

    if (warp > N_CONS_WARPS + 2 && !owner) return;
    if (tid == N_CONS + 32) {
#pragma unroll
        for (int i = 0; i < N_SLOT; i++) mbar_init(bar_empty + i * 8, RELEASE);
        asm volatile("fence.mbarrier_init.release.cluster;" ::: "memory");
    }
    if (tid == N_CONS + 64) {
#pragma unroll
        for (int i = BAR_GO; i < BAR_READY; i += 8) mbar_init(bar + i, 1);
#pragma unroll
        for (int i = BAR_HALF; i < BAR_READY; i += 8) mbar_expect_tx(bar + i, PIECE_BYTES);
        mbar_expect_tx(bar + BAR_X, D_MODEL * 2 + 4);
        mbar_expect_tx(bar + BAR_Q, (1 + tri) * CL * D_HEAD * 4);
        mbar_expect_tx(bar + BAR_ML, n_heads * CL * 8);
#pragma unroll
        for (int i = BAR_O; i <= BAR_S; i += 8) mbar_expect_tx(bar + i, 1024);
        asm volatile("fence.mbarrier_init.release.cluster;" ::: "memory");
    }
    __syncwarp();
    cluster_arrive();
    float* sst = reinterpret_cast<float*>(sp + SM_ST);
    if (tid < 8) *reinterpret_cast<uint2*>(sp + SM_XN + D_MODEL * 2 + tid * 8) = make_uint2(0u, 0u);
    if (rank == CL - 1 && warp >= V_WARPS && warp < N_CONS_WARPS) {
        if (warp == V_WARPS) {
            const uint32_t ep = ll_ld(g_epoch);
            cluster_wait();
            if (lane < CL) st_async(mapa(sb + SM_EPOCH, lane), __uint_as_float(ep), mapa(bar + BAR_X, lane));
        } else {
            uint2 u[5];
#pragma unroll
            for (int i = 0; i < 5; i++) u[i] = *reinterpret_cast<const uint2*>(prm.x + i * 128 + lane * 4);
            float s = 0.f;
#pragma unroll
            for (int i = 0; i < 5; i++) s += (bf_lo(u[i].x) + bf_hi(u[i].x)) + (bf_lo(u[i].y) + bf_hi(u[i].y));
#pragma unroll
            for (int o = 16; o > 0; o >>= 1) s += __shfl_xor_sync(0xffffffffu, s, o);
            const float mean = s * (1.f / D_MODEL);
            s = 0.f;
#pragma unroll
            for (int i = 0; i < 5; i++) {
                const float a = bf_lo(u[i].x) - mean, b = bf_hi(u[i].x) - mean, c = bf_lo(u[i].y) - mean, d = bf_hi(u[i].y) - mean;
                s += fmaf(a, a, b * b) + fmaf(c, c, d * d);
            }
#pragma unroll
            for (int o = 16; o > 0; o >>= 1) s += __shfl_xor_sync(0xffffffffu, s, o);
            const float mean_b = bf16r(mean);
            float den;
            asm("sqrt.approx.f32 %0, %1;" : "=f"(den) : "f"(bf16r(bf16r(s * (1.f / D_MODEL)) + 1e-5f)));
            const float inv = rcp(bf16r(den));
#pragma unroll
            for (int i = 0; i < 5; i++) {
                const uint32_t d0 = pack_bf16(bf_lo(u[i].x) - mean_b, bf_hi(u[i].x) - mean_b);
                const uint32_t d1 = pack_bf16(bf_lo(u[i].y) - mean_b, bf_hi(u[i].y) - mean_b);
                u[i] = make_uint2(pack_bf16(bf_lo(d0) * inv, bf_hi(d0) * inv), pack_bf16(bf_lo(d1) * inv, bf_hi(d1) * inv));
            }
            cluster_wait();
#pragma unroll 1
            for (int d = 0; d < CL; d++) {
                const uint32_t dst = mapa(sb + SM_XN + lane * 8, d), mb = mapa(bar + BAR_X, d);
#pragma unroll
                for (int i = 0; i < 5; i++) st_async2(dst + i * 256, __uint_as_float(u[i].x), __uint_as_float(u[i].y), mb);
            }
        }
        __syncwarp();
    }
    if (warp == N_CONS_WARPS + 1 ? rank >= V_WARPS : warp > N_CONS_WARPS && !owner) {
        named_arrive(6, n_start);
        return;
    }
    named_sync(6, n_start);
    if (tid == 0) mbar_arrive(bar + BAR_READY);
    mbar_wait(bar + BAR_X, 0);
    const uint32_t epoch = lds32(sb + SM_EPOCH);
    const uint32_t tag = 1u + (epoch & 1u);

    if (warp == N_CONS_WARPS + 1) {
        const bool fin = owner && rank < 4;
        const int col = oc * 64 + rank * 16 + (lane & 1) * 8 + ((lane >> 1) & 7);
        uint16_t* const out = reinterpret_cast<uint16_t*>(prm.out) + col;
        mbar_wait(bar + BAR_ML, 0);
        uint32_t xv = 0;
        if (fin) xv = reinterpret_cast<const uint16_t*>(prm.x)[col];
        float wv;
        {
            const uint32_t ma = sb + SM_ML + (lane < n_heads * CL ? lane : 0) * 8;
            const float mi = lds_f(ma);
            float m = fmaxf(mi, __shfl_xor_sync(0xffffffffu, mi, 1));
            m = fmaxf(m, __shfl_xor_sync(0xffffffffu, m, 2));
            m = fmaxf(m, __shfl_xor_sync(0xffffffffu, m, 4));
            const float ei = ex2((mi - m) * LOG2E);
            float den = ei * lds_f(ma + 4);
            den += __shfl_xor_sync(0xffffffffu, den, 1);
            den += __shfl_xor_sync(0xffffffffu, den, 2);
            den += __shfl_xor_sync(0xffffffffu, den, 4);
            wv = ei * rcp(den);
        }
#pragma unroll 1
        for (int hh = 0; hh < n_heads; hh++) {
            float w[CL];
#pragma unroll
            for (int s = 0; s < CL; s++) w[s] = __shfl_sync(0xffffffffu, wv, hh * CL + s);
            uint32_t* dst = g_x + D_FF + head_at(cl, hh, tri) * D_HEAD + rank * 32 + lane;
            const uint32_t src = sb + SM_OP + hh * 1024 + lane * 4;
            mbar_wait(bar + BAR_O + hh * 8, 0);
            float v[CL];
#pragma unroll
            for (int s = 0; s < CL; s++) v[s] = lds_f(src + s * 128);
            const float o = (fmaf(w[1], v[1], w[0] * v[0]) + fmaf(w[3], v[3], w[2] * v[2])) +
                            (fmaf(w[5], v[5], w[4] * v[4]) + fmaf(w[7], v[7], w[6] * v[6]));
            ll_store(dst, __float_as_uint(bf16r(o)) | tag);
        }
        if (fin) {
            mbar_wait(bar + BAR_G, 0);
            const uint32_t g = pack_bf16(silu_f(bf16r(lds_colsum(sb + SM_FG, lane))), 0.f);
            asm volatile("{\n.reg .pred p;\nsetp.eq.u32 p, %2, 0;\n@p st.relaxed.gpu.global.b32 [%0], %1;\n}" ::"l"(g_epoch), "r"(epoch + 1u), "r"(oc + rank + lane) : "memory");
            mbar_wait(bar + BAR_S, 0);
            uint32_t res = pack_bf16(lds_colsum(sb + SM_FS, lane), 0.f);
            asm("mul.rn.bf16x2 %0, %0, %1;" : "+r"(res) : "r"(g));
            asm("add.rn.bf16x2 %0, %0, %1;" : "+r"(res) : "r"(xv));
            if (lane < 16) *out = (uint16_t)res;
        }
        return;
    }
    if (warp >= N_CONS_WARPS + 2) {
        const int gw = warp - (N_CONS_WARPS + 2);
        mbar_wait(bar + BAR_GO, 0);
#pragma unroll 1
        for (int round = 0; round < 2; round++) {
            const int i0 = round * 4 + 2 + gw;
            const uint32_t* src0 = g_x + tail_row(rank, i0) + lane * 4;
            const uint32_t* src1 = g_x + tail_row(rank, gw) + lane * 4;
            if (round == 1) {
                named_arrive(8, N_CONS + N_GATHER);
                mbar_wait(bar + BAR_GO + 8, 0);
            }
            uint4 v0 = make_uint4(0u, 0u, 0u, 0u), v1 = v0;
            const bool second = round == 0 && gw < 2 && lane < 24;
            uint32_t miss0 = lane < 24, miss1 = second;
            unsigned n = 0;
#pragma unroll 1
            while (true) {
                ll_ld4_if(v0, src0, miss0);
                ll_ld4_if(v1, src1, miss1);
                if (ll_bad4(v0, tag) == 0) miss0 = 0;
                if (ll_bad4(v1, tag) == 0) miss1 = 0;
                if (__all_sync(0xffffffffu, (miss0 | miss1) == 0) || ++n > SPIN_LIMIT) break;
            }
            if (lane < 24)
                *reinterpret_cast<uint2*>(sp + SM_OV + i0 * 192 + lane * 8) = make_uint2(__byte_perm(v0.x, v0.y, 0x7632), __byte_perm(v0.z, v0.w, 0x7632));
            if (second)
                *reinterpret_cast<uint2*>(sp + SM_OV + gw * 192 + lane * 8) = make_uint2(__byte_perm(v1.x, v1.y, 0x7632), __byte_perm(v1.z, v1.w, 0x7632));
        }
        named_arrive(3, N_CONS + N_GATHER);
        return;
    }


    const int q4 = lane & 3, g8 = lane >> 2;
    const int rowT = (lane & 7) + ((lane >> 4) << 3), hiT = (lane >> 3) & 1;
    const uint32_t off_v = ((3 * rowT + (warp >> 1)) * 128 + ((hiT ^ ((3 * rowT + (warp >> 1)) & 7)) << 4)) ^ ((warp & 1) << 6);

    if (warp < V_WARPS) {
#pragma unroll 1
        for (int part = 0; part <= tri; part++) {
            const uint32_t xa = sb + SM_XN + ((part ? rank * 16 - 1280 : (rank & 3) * 16) + 2 * q4) * 2, xs = 128 << part;
            float acc[2][4] = {};
#pragma unroll 1
            for (int p = part * 10; p < 10 + part * 5; p++) {
                const uint32_t b0 = lds32(xa + p * xs), b1 = lds32(xa + p * xs + 16);
                mbar_wait(bar_full + (p >> 1) * 8, 0);
                uint32_t a[4];
                ldsm_x4_t(a, sb + SM_RING + p * PIECE_BYTES + off_v);
                mma_bf16(acc[0], a, b0, b1);
                ldsm_x4_t(a, sb + SM_RING + p * PIECE_BYTES + (off_v ^ 32));
                mma_bf16(acc[1], a, b0, b1);
                __syncwarp();
                if (lane == 0) mbar_arrive_n(bar_empty + (p >> 1) * 8, p == 14 ? RELEASE / V_WARPS : RELEASE / V_WARPS / 2);
            }
            const float v = pick4(acc[0][0], acc[0][2], acc[1][0], acc[1][2], q4);
            const uint32_t dst = sb + SM_QP + ((part * CL + rank) * D_HEAD + warp * 32 + q4 * 8 + g8) * 4;
#pragma unroll
            for (int d = 0; d < CL; d++) st_async(mapa(dst, d), v, mapa(bar + BAR_Q, d));
        }
        mbar_wait(bar + BAR_Q, 0);
        const float* qp = reinterpret_cast<const float*>(sp + SM_QP) + tid;
        __nv_bfloat16* qs = reinterpret_cast<__nv_bfloat16*>(sp + SM_Q) + tid;
        qs[0] = __float2bfloat16_rn((qp[0] + qp[192]) + (qp[384] + qp[576]));
        qs[(tri + 1) * D_HEAD] = __float2bfloat16_rn((qp[768] + qp[960]) + (qp[1152] + qp[1344]));
        if (tri) {
            qp += CL * D_HEAD;
            qs[D_HEAD] = __float2bfloat16_rn(((qp[0] + qp[192]) + (qp[384] + qp[576])) + ((qp[768] + qp[960]) + (qp[1152] + qp[1344])));
        }
    }
    named_sync(1, N_CONS);

    {
        const int rowN = (lane & 7) + (((lane >> 3) & 1) << 3), hiN = lane >> 4;
#pragma unroll 1
        for (int hh = 0; hh < n_heads; hh++) {
            float s0 = 0.f, s1 = 0.f;
#pragma unroll 1
            for (int i = 0; i < 2; i++) {
                const int u = hh * HEAD_TILES + i * 8 + warp, pos = pos_k + u, slot = pos & (N_SLOT - 1);
                mbar_wait(bar_full + slot * 8, (pos >> 4) & 1);
                const uint32_t tb = sb + SM_RING + slot * TILE_BYTES;
                float acc[2][2][4] = {};
#pragma unroll 1
                for (int j = 0; j < 3; j++) {
                    const int swz = u < 2 ? 0 : (3 * rowN + j) & 7;
                    const uint32_t oj = tb + (3 * rowN + j) * 128 + ((hiN ^ swz) << 4);
                    const uint32_t qa = sb + SM_Q + (hh * D_HEAD + j * 64 + 2 * q4) * 2;
#pragma unroll
                    for (int k = 0; k < 4; k++) {
                        const uint32_t b0 = lds32(qa + k * 32), b1 = lds32(qa + k * 32 + 16);
                        uint32_t a[4];
                        ldsm_x4(a, oj ^ (k << 5));
                        mma_bf16(acc[0][k & 1], a, b0, b1);
                        ldsm_x4(a, (oj + PIECE_BYTES) ^ (k << 5));
                        mma_bf16(acc[1][k & 1], a, b0, b1);
                    }
                }
                __syncwarp();
                if (lane == 0) mbar_arrive_n(bar_empty + slot * 8, RELEASE);
                const float raw = pick4(acc[0][0][0] + acc[0][1][0], acc[0][0][2] + acc[0][1][2],
                                        acc[1][0][0] + acc[1][1][0], acc[1][0][2] + acc[1][1][2], q4);
                s0 = s1;
                s1 = bf16r(bf16r(raw) * 0.07216878364870323f);
            }
            float m = fmaxf(s0, s1);
#pragma unroll
            for (int o = 16; o > 0; o >>= 1) m = fmaxf(m, __shfl_xor_sync(0xffffffffu, m, o));
            if (lane == 0) sst[hh * 8 + warp] = m;
            named_sync(1, N_CONS);
#pragma unroll
            for (int w = 0; w < 8; w++) m = fmaxf(m, sst[hh * 8 + w]);
            const float p0 = ex2((s0 - m) * LOG2E), p1 = ex2((s1 - m) * LOG2E);
            float l = p0 + p1;
#pragma unroll
            for (int o = 16; o > 0; o >>= 1) l += __shfl_xor_sync(0xffffffffu, l, o);
            if (lane == 0) sst[24 + hh * 8 + warp] = l;
            __nv_bfloat16* ps = reinterpret_cast<__nv_bfloat16*>(sp + SM_P) + hh * 512 + warp * 32 + q4 * 8 + g8;
            ps[0] = __float2bfloat16_rn(p0);
            ps[256] = __float2bfloat16_rn(p1);
        }
        named_sync(1, N_CONS);
        if (warp == 7 && lane < n_heads * CL && (lane & 7) < V_WARPS) {
            const float* st = sst + (lane & 24);
            float m = st[0], l = st[24];
#pragma unroll
            for (int w = 1; w < 8; w++) { m = fmaxf(m, st[w]); l += st[24 + w]; }
            st_async2(mapa(sb + SM_ML + ((lane & 24) + rank) * 8, lane & 7), m, l, mapa(bar + BAR_ML, lane & 7));
        }
    }

    const uint32_t off_w = (warp >> 2) * PIECE_BYTES + rowT * 128 + (((((warp & 3) << 1) | hiT) ^ (rowT & 7)) << 4);

    if (ffn) {
#pragma unroll 1
        for (int res = 0; res < 2; res++) {
            float acc[3][4] = {};
#pragma unroll 1
            for (int i = 0; i < W_TILES / 2; i++) {
                const int pos = pos_w + res * (W_TILES / 2) + i, slot = pos & (N_SLOT - 1);
                const uint32_t xa = sb + SM_XN + (i * 96 + (warp >> 2) * 48 + 2 * q4) * 2;
                mbar_wait(bar_full + slot * 8, (pos >> 4) & 1);
#pragma unroll
                for (int k = 0; k < 3; k++) {
                    uint32_t a[4];
                    ldsm_x4_t(a, sb + SM_RING + slot * TILE_BYTES + off_w + k * 2048);
                    mma_bf16(acc[k], a, lds32(xa + k * 32), lds32(xa + k * 32 + 16));
                }
                __syncwarp();
                if (lane == 0) mbar_arrive_n(bar_empty + slot * 8, RELEASE / N_CONS_WARPS);
            }
            if (q4 < 2)
                reinterpret_cast<float*>(sp + SM_FG)[res * 128 + warp * 16 + q4 * 8 + g8] =
                    q4 ? (acc[0][2] + acc[1][2]) + acc[2][2] : (acc[0][0] + acc[1][0]) + acc[2][0];
        }
        named_sync(1, N_CONS);
        if (warp >= V_WARPS) {
            const float* f = reinterpret_cast<const float*>(sp + SM_FG) + (tid & 63);
            const float h = bf16r(bf16r(silu_f(bf16r(f[0] + f[64]))) * bf16r(f[128] + f[192]));
            ll_store(g_x + (cta - CL_FFN * CL) * 64 + (tid & 63), __float_as_uint(h) | tag);
        }
    }

    if (warp < V_WARPS) {
        const uint32_t rdst = mapa(sb + SM_OP + rank * 128 + (q4 * 8 + g8) * 4, warp), rbar = mapa(bar + BAR_O, warp);
#pragma unroll 1
        for (int hh = 0; hh < n_heads; hh++) {
            float oacc[2][2][4] = {};
#pragma unroll 2
            for (int u = hh * HEAD_TILES; u < (hh + 1) * HEAD_TILES; u++) {
                const int pos = pos_v + u, slot = pos & (N_SLOT - 1);
                uint32_t ta = sb + SM_RING + slot * TILE_BYTES + off_v, tc = ta ^ 32;
                asm volatile("" : "+r"(ta), "+r"(tc));
                const uint32_t pa = sb + SM_P + (u * 32 + 2 * q4) * 2;
                const uint32_t b0 = lds32(pa), b1 = lds32(pa + 16), b2 = lds32(pa + 32), b3 = lds32(pa + 48);
                mbar_wait(bar_full + slot * 8, (pos >> 4) & 1);
                uint32_t a[4][4];
                ldsm_x4_t(a[0], ta);
                ldsm_x4_t(a[1], tc);
                ldsm_x4_t(a[2], ta + PIECE_BYTES);
                ldsm_x4_t(a[3], tc + PIECE_BYTES);
                mma_bf16(oacc[0][0], a[0], b0, b1);
                mma_bf16(oacc[1][0], a[1], b0, b1);
                mma_bf16(oacc[0][1], a[2], b2, b3);
                mma_bf16(oacc[1][1], a[3], b2, b3);
                __syncwarp();
                if (lane == 0) mbar_arrive_n(bar_empty + slot * 8, RELEASE / V_WARPS);
            }
            const float v = pick4(oacc[0][0][0] + oacc[0][1][0], oacc[0][0][2] + oacc[0][1][2],
                                  oacc[1][0][0] + oacc[1][1][0], oacc[1][0][2] + oacc[1][1][2], q4);
            st_async(rdst + hh * 1024, v, rbar + hh * 8);
        }
    }
    if (!owner) return;

    {
        const uint32_t rdst = mapa(sb + SM_FG + (rank * 2 + (warp >> 2)) * 64 + g8 * 8, warp & 3);
        const uint32_t rbar = mapa(bar + BAR_G, warp & 3);
        const uint32_t va = sb + SM_OV + ((warp >> 2) * 48 + 2 * q4) * 2, tw = sb + SM_RING + SLOT_T * TILE_BYTES + off_w;
        named_sync(8, N_CONS + N_GATHER);
        auto send = [&](const float (&acc)[3][4], uint32_t dst, uint32_t mb) {
            if (q4 == 0) st_async2(dst, (acc[0][0] + acc[1][0]) + acc[2][0], (acc[0][2] + acc[1][2]) + acc[2][2], mb);
        };
        float acc[3][4] = {};
#pragma unroll 1
        for (int i = 0; i < 6; i++) {
            uint32_t b[3][2];
#pragma unroll
            for (int k = 0; k < 3; k++) { b[k][0] = lds32(va + i * 192 + k * 32); b[k][1] = lds32(va + i * 192 + k * 32 + 16); }
            mbar_wait(bar_full + (SLOT_T + i) * 8, 0);
#pragma unroll
            for (int k = 0; k < 3; k++) {
                uint32_t a[4];
                ldsm_x4_t(a, tw + i * TILE_BYTES + k * 2048);
                mma_bf16(acc[k], a, b[k][0], b[k][1]);
            }
            if (i == 1) {
                send(acc, rdst, rbar);
#pragma unroll
                for (int k = 0; k < 3; k++) acc[k][0] = acc[k][1] = acc[k][2] = acc[k][3] = 0.f;
            }
        }
        const uint32_t hb = warp < 4 ? bar_full + (SLOT_T + 6) * 8 : bar + BAR_HALF;
        uint32_t a[4][3][4], b[4][3][2];
        named_sync(3, N_CONS + N_GATHER);
#pragma unroll
        for (int i = 0; i < 4; i++)
#pragma unroll
            for (int k = 0; k < 3; k++) { b[i][k][0] = lds32(va + (6 + i) * 192 + k * 32); b[i][k][1] = lds32(va + (6 + i) * 192 + k * 32 + 16); }
#pragma unroll
        for (int i = 0; i <= 4; i++) {
            if (i < 4) {
                mbar_wait(hb + i * 8, 0);
#pragma unroll
                for (int k = 0; k < 3; k++) ldsm_x4_t(a[i][k], tw + (6 + i) * TILE_BYTES + k * 2048);
            }
            if (i >= 1) {
#pragma unroll
                for (int k = 0; k < 3; k++) mma_bf16(acc[k], a[i - 1][k], b[i - 1][k][0], b[i - 1][k][1]);
            }
        }
        send(acc, rdst + (SM_FS - SM_FG), rbar + (BAR_S - BAR_G));
    }
}

typedef CUresult (*EncodeTiledFn)(CUtensorMap*, CUtensorMapDataType, cuuint32_t, void*, const cuuint64_t*,
                                  const cuuint64_t*, const cuuint32_t*, const cuuint32_t*, CUtensorMapInterleave,
                                  CUtensorMapSwizzle, CUtensorMapL2promotion, CUtensorMapFloatOOBfill);

void encode_map(EncodeTiledFn fn, CUtensorMap* m, const void* base, cuuint64_t rows, cuuint64_t cols, cuuint32_t b1, cuuint32_t b2) {
    const cuuint64_t dims[3] = {64, cols / 64, rows};
    const cuuint64_t strides[2] = {128, cols * 2};
    const cuuint32_t box[3] = {64, b1, b2};
    const cuuint32_t estr[3] = {1, 1, 1};
    fn(m, CU_TENSOR_MAP_DATA_TYPE_BFLOAT16, 3, const_cast<void*>(base), dims, strides, box, estr,
       CU_TENSOR_MAP_INTERLEAVE_NONE, CU_TENSOR_MAP_SWIZZLE_128B, CU_TENSOR_MAP_L2_PROMOTION_NONE,
       CU_TENSOR_MAP_FLOAT_OOB_FILL_NONE);
}

}

extern "C" void kernel_launch(void* const* d_in, const int* in_sizes, int n_in, void* d_out, int out_size) {
    (void)in_sizes; (void)n_in; (void)out_size;
    static EncodeTiledFn encode = nullptr;
    static double pace_scale = 1.0;
    static void* scratch = nullptr;
    if (!encode) {
        int dev = 0, mem_khz = 0, bus_bits = 0;
        cudaGetDevice(&dev);
        cudaDeviceGetAttribute(&mem_khz, cudaDevAttrMemoryClockRate, dev);
        cudaDeviceGetAttribute(&bus_bits, cudaDevAttrGlobalMemoryBusWidth, dev);
        const double peak_gbs = 2.0 * mem_khz * 1e-6 * bus_bits / 8.0;
        if (peak_gbs > 0.0) pace_scale = PACE_REF_GBS / peak_gbs;
        void* fn = nullptr;
        cudaDriverEntryPointQueryResult qr;
        cudaGetDriverEntryPoint("cuTensorMapEncodeTiled", &fn, cudaEnableDefault, &qr);
        encode = reinterpret_cast<EncodeTiledFn>(fn);
        cudaFuncSetAttribute(fused_decode_kernel, cudaFuncAttributeMaxDynamicSharedMemorySize, SM_ALLOC);
        cudaGetSymbolAddress(&scratch, g_scratch);
    }
    CUtensorMap tm_k, tm_v, tm_wq, tm_w1, tm_w3, tm_wo, tm_w2;
    encode_map(encode, &tm_k, d_in[1], (cuuint64_t)N_HEAD * SEQ, D_HEAD, 3, 32);
    encode_map(encode, &tm_v, d_in[2], (cuuint64_t)N_HEAD * SEQ, D_HEAD, 3, 32);
    encode_map(encode, &tm_wq, d_in[3], D_MODEL, N_HEAD * D_HEAD, 3, 16);
    encode_map(encode, &tm_w1, d_in[6], D_MODEL, D_FF, 1, 96);
    encode_map(encode, &tm_w3, d_in[7], D_MODEL, D_FF, 1, 96);
    encode_map(encode, &tm_wo, d_in[4], N_HEAD * D_HEAD, D_MODEL, 1, 48);
    encode_map(encode, &tm_w2, d_in[8], D_FF, D_MODEL, 1, 48);
    Params prm;
    prm.x = static_cast<const __nv_bfloat16*>(d_in[0]);
    prm.out = static_cast<__nv_bfloat16*>(d_out);
    prm.k = static_cast<const __nv_bfloat16*>(d_in[1]) + (size_t)(SEQ - WIN) * D_HEAD;
    prm.scratch = static_cast<uint32_t*>(scratch);
    auto step = [&](double pace, double bytes, int pieces) { return (uint16_t)(8.0 * pace * pace_scale * bytes / (128.0 * TILE_BYTES) / pieces); };
    const double b_wq = 2.0 * D_MODEL * N_HEAD * D_HEAD;
    const double b_mid = 4.0 * N_HEAD * WIN * D_HEAD - 2.0 * N_CTA * TILE_BYTES + 4.0 * D_MODEL * D_FF;
    const double b_tail = 2.0 * D_MODEL * (D_FF + N_HEAD * D_HEAD);
    prm.step_wq2 = step(PACE_HEAD, b_wq, 10);
    prm.step_wq3 = step(PACE_HEAD, b_wq, 15);
    prm.step_own = step(PACE_MID, b_mid, 4 * HEAD_TILES - 2);
    prm.step_ffn = step(PACE_MID, b_mid, 4 * HEAD_TILES - 2 + W_TILES);
    prm.step_tri = step(PACE_MID, b_mid, 6 * HEAD_TILES - 2);
    prm.step_tail = step(PACE_TAIL, b_tail, TAIL_TILES);
    prm.late = (uint16_t)(4096.0 * PACE_LATE / PACE_MID + 0.5);
    prm.pad = 0;
    fused_decode_kernel<<<N_CTA, N_THREADS, SM_ALLOC, cudaStreamPerThread>>>(prm, tm_wq, tm_w1, tm_w3, tm_k, tm_v, tm_wo, tm_w2);
}
```

```cpp
#include <cuda_runtime.h>
#include <cuda_bf16.h>
#include <cuda.h>
#include <stdint.h>

namespace {

constexpr int D_MODEL = 640;
constexpr int N_HEAD = 32;
constexpr int D_HEAD = 192;
constexpr int SEQ = 32768;
constexpr int WIN = 4096;
constexpr int D_FF = 1536;

constexpr int CL = 8;
constexpr int N_CL = 15;
constexpr int N_CTA = CL * N_CL;
constexpr int CL_FFN = 4, CL_TRI = CL_FFN + 3, CL_OWN = CL_TRI + 2;
constexpr int TILE_BYTES = 12288;
constexpr int PIECE_BYTES = TILE_BYTES / 2;
constexpr int N_SLOT = 16;
constexpr int HEAD_TILES = WIN / CL / 32;
constexpr int W_TILES = 14;
constexpr int TAIL_TILES = 10;
constexpr int POS_K2 = 5, POS_K3 = 8;
constexpr int POS_T = POS_K2 + 4 * HEAD_TILES, SLOT_T = POS_T % N_SLOT;
static_assert(SLOT_T + TAIL_TILES <= N_SLOT && (POS_T / N_SLOT) % 2 == 0, "the tail uses consecutive slots in a phase of parity 0");

constexpr int N_CONS_WARPS = 8;
constexpr int N_CONS = N_CONS_WARPS * 32;
constexpr int N_GATHER = 128;
constexpr int N_THREADS = N_CONS + 64 + N_GATHER;
constexpr int V_WARPS = 6;
constexpr int RELEASE = 24;

constexpr double PACE_HEAD = 490, PACE_MID = 479, PACE_LATE = 495, PACE_TAIL = 484, PACE_REF_GBS = 3352.32;
constexpr int START_DELAY = 140;
constexpr int WINDOW_OWN = 5, WINDOW_FFN = 6, WINDOW_TRI = 8;
constexpr int SLIP = 200;
constexpr int GATE_EARLY = 4, GATE_LATE = 7;

constexpr unsigned SPIN_LIMIT = 1u << 22;

constexpr int SM_RING = 0;
constexpr int SM_BAR = N_SLOT * TILE_BYTES;
constexpr int BAR_FULL = 0, BAR_EMPTY = 128, BAR_GO = 256, BAR_Q = 272, BAR_ML = 280, BAR_O = 288, BAR_G = 312, BAR_S = 320, BAR_X = 328,
              BAR_HALF = 336, BAR_READY = 368;
constexpr int SM_T0 = SM_BAR + 448, SM_EPOCH = SM_BAR + 452;
constexpr int SM_XN = SM_BAR + 512;
constexpr int SM_Q = SM_XN + 1408;
constexpr int SM_ST = SM_Q + 1152;
constexpr int SM_ML = SM_ST + 256;
constexpr int SM_P = SM_ML + 256;
constexpr int SM_QP = SM_P + 3072;
constexpr int SM_OP = SM_QP + 12288;
constexpr int SM_OV = SM_OP + 3072;
constexpr int SM_FG = SM_OV + 1920;
constexpr int SM_FS = SM_FG + 1024;
constexpr int SM_ALLOC = SM_FS + 1024 + 1024;

constexpr int XO_H = 32;
constexpr int XO_END = XO_H + D_FF + N_HEAD * D_HEAD;
__device__ __align__(128) uint32_t g_scratch[XO_END];

__device__ __forceinline__ uint32_t smem_u32(const void* p) { return (uint32_t)__cvta_generic_to_shared(p); }

__device__ __forceinline__ void mbar_init(uint32_t bar, uint32_t cnt) {
    asm volatile("mbarrier.init.shared::cta.b64 [%0], %1;" ::"r"(bar), "r"(cnt) : "memory");
}
__device__ __forceinline__ void mbar_expect_tx(uint32_t bar, uint32_t bytes) {
    asm volatile("mbarrier.arrive.expect_tx.shared::cta.b64 _, [%0], %1;" ::"r"(bar), "r"(bytes) : "memory");
}
__device__ __forceinline__ void mbar_arrive(uint32_t bar) {
    asm volatile("mbarrier.arrive.shared::cta.b64 _, [%0];" ::"r"(bar) : "memory");
}
__device__ __forceinline__ void mbar_wait(uint32_t bar, uint32_t parity) {
    asm volatile(
        "{\n.reg .pred p, q;\n.reg .u32 n;\n"
        "mov.u32 n, 0;\n"
        "WAIT_LOOP:\n"
        "add.u32 n, n, 1;\n"
        "setp.lt.u32 q, n, %2;\n"
        "mbarrier.try_wait.parity.shared::cta.b64 p, [%0], %1;\n"
        "and.pred q, q, !p;\n"
        "@q bra WAIT_LOOP;\n}"
        ::"r"(bar), "r"(parity), "n"(SPIN_LIMIT) : "memory");
}
__device__ __forceinline__ void named_sync(int id, int n) {
    asm volatile("bar.sync %0, %1;" ::"r"(id), "r"(n) : "memory");
}
__device__ __forceinline__ void named_arrive(int id, int n) {
    asm volatile("bar.arrive %0, %1;" ::"r"(id), "r"(n) : "memory");
}
__device__ __forceinline__ uint64_t stream_policy() {
    uint64_t pol;
    asm volatile("createpolicy.fractional.L2::evict_first.b64 %0, 1.0;" : "=l"(pol));
    return pol;
}
__device__ __forceinline__ void bulk_load(uint32_t dst, const void* src, uint32_t bytes, uint32_t bar, uint64_t pol) {
    asm volatile("cp.async.bulk.shared::cluster.global.mbarrier::complete_tx::bytes.L2::cache_hint [%0], [%1], %2, [%3], %4;"
                 ::"r"(dst), "l"(src), "r"(bytes), "r"(bar), "l"(pol) : "memory");
}
__device__ __forceinline__ void tma_3d(uint32_t dst, const CUtensorMap* tm, int c0, int c1, int c2, uint32_t bar, uint64_t pol) {
    asm volatile("cp.async.bulk.tensor.3d.shared::cluster.global.mbarrier::complete_tx::bytes.L2::cache_hint [%0], [%1, {%3, %4, %5}], [%2], %6;"
                 ::"r"(dst), "l"(tm), "r"(bar), "r"(c0), "r"(c1), "r"(c2), "l"(pol) : "memory");
}
__device__ __forceinline__ void prefetch_tmap(const CUtensorMap* tm) {
    asm volatile("prefetch.tensormap [%0];" ::"l"(tm) : "memory");
}
__device__ __forceinline__ void ldsm_x4(uint32_t (&r)[4], uint32_t addr) {
    asm volatile("ldmatrix.sync.aligned.m8n8.x4.shared.b16 {%0,%1,%2,%3}, [%4];"
                 : "=r"(r[0]), "=r"(r[1]), "=r"(r[2]), "=r"(r[3]) : "r"(addr) : "memory");
}
__device__ __forceinline__ void ldsm_x4_t(uint32_t (&r)[4], uint32_t addr) {
    asm volatile("ldmatrix.sync.aligned.m8n8.x4.trans.shared.b16 {%0,%1,%2,%3}, [%4];"
                 : "=r"(r[0]), "=r"(r[1]), "=r"(r[2]), "=r"(r[3]) : "r"(addr) : "memory");
}
__device__ __forceinline__ void mma_bf16(float (&c)[4], const uint32_t (&a)[4], uint32_t b0, uint32_t b1) {
    asm volatile("mma.sync.aligned.m16n8k16.row.col.f32.bf16.bf16.f32 {%0,%1,%2,%3}, {%4,%5,%6,%7}, {%8,%9}, {%0,%1,%2,%3};"
                 : "+f"(c[0]), "+f"(c[1]), "+f"(c[2]), "+f"(c[3])
                 : "r"(a[0]), "r"(a[1]), "r"(a[2]), "r"(a[3]), "r"(b0), "r"(b1));
}
__device__ __forceinline__ float bf16r(float v) {
    uint32_t p;
    asm("cvt.rn.bf16x2.f32 %0, %1, %2;" : "=r"(p) : "f"(v), "f"(0.f));
    return __uint_as_float(p);
}
__device__ __forceinline__ uint32_t lds32(uint32_t addr) {
    uint32_t v;
    asm volatile("ld.shared.b32 %0, [%1];" : "=r"(v) : "r"(addr) : "memory");
    return v;
}
__device__ __forceinline__ float bf_lo(uint32_t v) { return __uint_as_float(v << 16); }
__device__ __forceinline__ float bf_hi(uint32_t v) { return __uint_as_float(v & 0xffff0000u); }
__device__ __forceinline__ uint32_t pack_bf16(float lo, float hi) {
    const __nv_bfloat162 p = __floats2bfloat162_rn(lo, hi);
    return *reinterpret_cast<const uint32_t*>(&p);
}
__device__ __forceinline__ uint32_t now_ns() {
    unsigned long long t;
    asm volatile("mov.u64 %0, %%globaltimer;" : "=l"(t));
    return (uint32_t)t;
}

__device__ __forceinline__ void wait_until(uint32_t t_start, uint32_t deadline) {
    unsigned n = 0;
    while (now_ns() - t_start < deadline && ++n < SPIN_LIMIT) {}
}

__device__ __forceinline__ uint32_t ll_bad4(const uint4& v, uint32_t tag) {
    uint32_t lo, hi;
    asm("lop3.b32 %0, %1, %2, %3, 0x7E;" : "=r"(lo) : "r"(v.x), "r"(v.y), "r"(tag));
    asm("lop3.b32 %0, %1, %2, %3, 0x7E;" : "=r"(hi) : "r"(v.z), "r"(v.w), "r"(tag));
    return (lo | hi) & 3u;
}
__device__ __forceinline__ float ex2(float v) {
    float r;
    asm("ex2.approx.ftz.f32 %0, %1;" : "=f"(r) : "f"(v));
    return r;
}
__device__ __forceinline__ float rcp(float v) {
    float r;
    asm("rcp.approx.ftz.f32 %0, %1;" : "=f"(r) : "f"(v));
    return r;
}
constexpr float LOG2E = 1.4426950408889634f;
__device__ __forceinline__ void ll_store(uint32_t* p, uint32_t w) {
    asm volatile("st.relaxed.gpu.global.b32 [%0], %1;" ::"l"(p), "r"(w) : "memory");
}
__device__ __forceinline__ uint32_t ll_ld(const uint32_t* p) {
    uint32_t v;
    asm volatile("ld.relaxed.gpu.global.b32 %0, [%1];" : "=r"(v) : "l"(p) : "memory");
    return v;
}
__device__ __forceinline__ float pick4(float a, float b, float c, float d, int j) {
    const float lo = (j & 1) ? b : a, hi = (j & 1) ? d : c;
    return (j & 2) ? hi : lo;
}
__device__ __forceinline__ float silu_f(float v) { return v * rcp(1.f + ex2(-LOG2E * v)); }

__device__ __forceinline__ void mbar_arrive_n(uint32_t bar, uint32_t n) {
    asm volatile("mbarrier.arrive.shared::cta.b64 _, [%0], %1;" ::"r"(bar), "r"(n) : "memory");
}
__device__ __forceinline__ uint32_t mapa(uint32_t addr, uint32_t rank) {
    uint32_t d;
    asm("mapa.shared::cluster.u32 %0, %1, %2;" : "=r"(d) : "r"(addr), "r"(rank));
    return d;
}
__device__ __forceinline__ void st_async(uint32_t dst, float v, uint32_t bar) {
    asm volatile("st.async.weak.shared::cluster.mbarrier::complete_tx::bytes.f32 [%0], %1, [%2];" ::"r"(dst), "f"(v), "r"(bar) : "memory");
}
__device__ __forceinline__ void st_async2(uint32_t dst, float a, float b, uint32_t bar) {
    asm volatile("st.async.weak.shared::cluster.mbarrier::complete_tx::bytes.v2.f32 [%0], {%1, %2}, [%3];" ::"r"(dst), "f"(a), "f"(b), "r"(bar) : "memory");
}
__device__ __forceinline__ void cluster_arrive() { asm volatile("barrier.cluster.arrive.relaxed.aligned;" ::: "memory"); }
__device__ __forceinline__ void cluster_wait() { asm volatile("barrier.cluster.wait.aligned;" ::: "memory"); }
__device__ __forceinline__ void ll_ld4_if(uint4& v, const uint32_t* p, uint32_t cond) {
    asm volatile("{\n.reg .pred p;\nsetp.ne.u32 p, %5, 0;\n@p ld.relaxed.gpu.global.v4.b32 {%0,%1,%2,%3}, [%4];\n}"
                 : "+r"(v.x), "+r"(v.y), "+r"(v.z), "+r"(v.w) : "l"(p), "r"(cond) : "memory");
}
__device__ __forceinline__ float lds_f(uint32_t addr) { return __uint_as_float(lds32(addr)); }
__device__ __forceinline__ float lds_colsum(uint32_t base, int lane) {
    const uint32_t addr = base + ((lane >> 3) ^ ((lane >> 2) & 1)) * 64 + (lane & 3) * 16;
    uint32_t v[4][4];
#pragma unroll
    for (int i = 0; i < 4; i++) ldsm_x4(v[i], addr + i * 256);
    float t[4];
#pragma unroll
    for (int i = 0; i < 4; i++)
        t[i] = (__uint_as_float(v[i][0]) + __uint_as_float(v[i][1])) + (__uint_as_float(v[i][2]) + __uint_as_float(v[i][3]));
    return ((t[0] + t[1]) + t[2]) + t[3];
}

constexpr uint32_t FIRST_MUL = 129, FIRST_MASK = 0x3c07;
__device__ __forceinline__ int pair_head(int cl, int j) { return cl + j * 16; }
__device__ __forceinline__ int third_head(int cl) { return 15 + (cl - CL_TRI) * 16; }
__device__ __forceinline__ int head_at(int cl, int hh, int tri) { return (hh & tri) ? third_head(cl) : pair_head(cl, hh >> tri); }
__device__ __forceinline__ int tail_row(int rank, int i) {
    return (i < 6 ? i : 6 + (i & 3)) * (CL * 96) + rank * 96;
}

struct Params {
    const __nv_bfloat16* x;
    __nv_bfloat16* out;
    const __nv_bfloat16* k;
    uint32_t* scratch;
    uint16_t step_wq2, step_wq3, step_own, step_ffn, step_tri, step_tail, late, pad;
};
static_assert(sizeof(Params) == 48, "Params must fill the rest of the first parameter line");

__global__ void __cluster_dims__(CL, 1, 1) __launch_bounds__(N_THREADS, 1)
fused_decode_kernel(const Params prm, const __grid_constant__ CUtensorMap tm_wq, const __grid_constant__ CUtensorMap tm_w1,
                    const __grid_constant__ CUtensorMap tm_w3, const __grid_constant__ CUtensorMap tm_k,
                    const __grid_constant__ CUtensorMap tm_v, const __grid_constant__ CUtensorMap tm_wo,
                    const __grid_constant__ CUtensorMap tm_w2) {
    extern __shared__ uint8_t smem_raw[];
    asm volatile("{\n.reg .pred p;\nsetp.lt.u32 p, %1, %2;\n@p prefetch.global.L2 [%0];\n}"
                 ::"l"(reinterpret_cast<const char*>(prm.k) + (size_t)(((blockIdx.x * FIRST_MUL) & FIRST_MASK) * (TILE_BYTES / 32) + threadIdx.x) * 32),
                   "r"(threadIdx.x), "n"(TILE_BYTES / 32) : "memory");
    const uint32_t sb = (smem_u32(smem_raw) + 1023u) & ~1023u;
    uint8_t* sp = smem_raw + (sb - smem_u32(smem_raw));
    const uint32_t bar = sb + SM_BAR;
    const uint32_t bar_full = bar + BAR_FULL, bar_empty = bar + BAR_EMPTY;

    const int tid = threadIdx.x;
    const int cta = blockIdx.x, cl = blockIdx.x / CL, rank = blockIdx.x % CL;
    const int tri = cl >= CL_TRI && cl < CL_OWN;
    const int pos_k = tri ? POS_K3 : POS_K2;
    volatile uint32_t* t_first = reinterpret_cast<volatile uint32_t*>(sp + SM_T0);
    if (tid == N_CONS) {
        const __nv_bfloat16* k0 = prm.k + (uint32_t)(pair_head(cl, 0) * SEQ + rank * 32) * (size_t)D_HEAD;
#pragma unroll
        for (int u = 1; u >= 0; u--) {
            const uint32_t fb = bar_full + (pos_k + u) * 8;
            mbar_init(fb, 1);
            asm volatile("fence.mbarrier_init.release.cluster;" ::: "memory");
            mbar_expect_tx(fb, TILE_BYTES);
            bulk_load(sb + SM_RING + (pos_k + u) * TILE_BYTES, k0 + u * (CL * 32 * D_HEAD), TILE_BYTES, fb, stream_policy());
            if (u == 1) *t_first = now_ns();
        }
    }
    if (tid == N_CONS + 32) prefetch_tmap(&tm_wq);
    const int warp = __shfl_sync(0xffffffffu, tid >> 5, 0), lane = tid & 31;
    const bool owner = cl < CL_FFN || cl >= CL_OWN, ffn = !owner && !tri;
    const int oc = cl < CL_FFN ? cl : cl - (CL_OWN - CL_FFN);
    const int n_heads = 2 + tri;
    const int pos_w = pos_k + n_heads * HEAD_TILES;
    const int pos_v = pos_w + (ffn ? W_TILES : 0);
    const int pos_t = pos_v + n_heads * HEAD_TILES;
    uint32_t* const g_epoch = prm.scratch;
    uint32_t* const g_x = prm.scratch + XO_H;
    const int n_start = owner ? N_THREADS : N_THREADS - 96;

    if (warp == N_CONS_WARPS) {
        if (lane == 0) {
#pragma unroll
            for (int i = 2; i < N_SLOT; i++) mbar_init(bar_full + ((pos_k + i) & (N_SLOT - 1)) * 8, 1);
            mbar_init(bar + BAR_READY, 1);
            asm volatile("fence.mbarrier_init.release.cluster;" ::: "memory");
        }
        __syncwarp();
        named_arrive(6, n_start);
        cluster_arrive();
        if (lane == 0) {
            const uint64_t pol = stream_policy();
            const uint32_t t_start = *t_first;
            uint32_t deadline = START_DELAY * 8;
            {
                const uint32_t step = tri ? prm.step_wq3 : prm.step_wq2;
#pragma unroll 1
                for (int p = 0; p < 10 + 5 * tri; p++) {
                    const uint32_t fb = bar_full + (p >> 1) * 8;
                    if (!(p & 1)) mbar_expect_tx(fb, p == 14 ? PIECE_BYTES : TILE_BYTES);
                    const int h = p < 10 ? pair_head(cl, rank >> 2) : third_head(cl);
                    const int row = p < 10 ? p * 64 + (rank & 3) * 16 : (p - 10) * 128 + rank * 16;
                    wait_until(t_start, deadline >> 3);
                    tma_3d(sb + SM_RING + p * PIECE_BYTES, &tm_wq, 0, h * 3, row, fb, pol);
                    deadline += step;
                }
            }
            mbar_wait(bar + BAR_READY, 0);
            uint32_t step = owner ? prm.step_own : (tri ? prm.step_tri : prm.step_ffn);
            const int window = owner ? WINDOW_OWN : (tri ? WINDOW_TRI : WINDOW_FFN);
            const int pos_late = pos_t - (owner ? 16 : (tri ? 24 : 20));
#pragma unroll 1
            for (int pos = pos_k + 2;; pos++) {
                if (pos >= pos_k + 2 + window) mbar_wait(bar_full + ((pos - window) & (N_SLOT - 1)) * 8, ((pos - window) >> 4) & 1);
                deadline = max(deadline, (now_ns() - t_start - SLIP) << 3);
                if (pos == pos_t) break;
                const int slot = pos & (N_SLOT - 1);
                const CUtensorMap* tm;
                int c1 = 0, row;
                if (pos >= pos_w && pos < pos_v) {
                    const bool up = pos >= pos_w + W_TILES / 2;
                    tm = up ? &tm_w3 : &tm_w1;
                    c1 = cta - CL_FFN * CL;
                    row = (pos - pos_w - (up ? W_TILES / 2 : 0)) * 96;
                } else {
                    const int u = pos - (pos < pos_w ? pos_k : pos_v), hh = u >> 4;
                    tm = pos < pos_w ? &tm_k : &tm_v;
                    row = head_at(cl, hh, tri) * SEQ + (SEQ - WIN) + rank * 32 + (u & 15) * (CL * 32);
                }
                if (pos >= N_SLOT) mbar_wait(bar_empty + slot * 8, ((pos >> 4) - 1) & 1);
                mbar_expect_tx(bar_full + slot * 8, TILE_BYTES);
                wait_until(t_start, deadline >> 3);
                tma_3d(sb + SM_RING + slot * TILE_BYTES, tm, 0, c1, row, bar_full + slot * 8, pol);
                deadline += step;
                if (pos == pos_late) step = step * prm.late >> 12;
                if (pos == pos_t - GATE_EARLY) mbar_arrive(bar + BAR_GO);
            }
            if (owner) {
                mbar_wait(bar_empty + (SLOT_T + TAIL_TILES - 1) * 8, ((POS_T >> 4) - 1) & 1);
#pragma unroll
                for (int i = 0; i < TAIL_TILES; i++) mbar_expect_tx(bar_full + (SLOT_T + i) * 8, i < 6 ? TILE_BYTES : PIECE_BYTES);
#pragma unroll 1
                for (int i = 0; i < TAIL_TILES; i++) {
                    const CUtensorMap* tm = i < 2 ? &tm_w2 : &tm_wo;
                    const int row = tail_row(rank, i) - (i < 2 ? 0 : D_FF);
                    const uint32_t dst = sb + SM_RING + (SLOT_T + i) * TILE_BYTES, fb = bar_full + (SLOT_T + i) * 8;
                    wait_until(t_start, deadline >> 3);
                    tma_3d(dst, tm, 0, oc, row, fb, pol);
                    tma_3d(dst + PIECE_BYTES, tm, 0, oc, row + 48, i < 6 ? fb : bar + BAR_HALF + (i - 6) * 8, pol);
                    if (i == GATE_LATE) {
                        wait_until(t_start, (deadline + prm.step_tail / 2) >> 3);
                        mbar_arrive(bar + BAR_GO + 8);
                    }
                    deadline += prm.step_tail;
                }
            }
        }
        return;
    }

    if (warp > N_CONS_WARPS + 2 && !owner) return;
    if (tid == N_CONS + 32) {
#pragma unroll
        for (int i = 0; i < N_SLOT; i++) mbar_init(bar_empty + i * 8, RELEASE);
        asm volatile("fence.mbarrier_init.release.cluster;" ::: "memory");
    }
    if (tid == N_CONS + 64) {
#pragma unroll
        for (int i = BAR_GO; i < BAR_READY; i += 8) mbar_init(bar + i, 1);
#pragma unroll
        for (int i = BAR_HALF; i < BAR_READY; i += 8) mbar_expect_tx(bar + i, PIECE_BYTES);
        mbar_expect_tx(bar + BAR_X, D_MODEL * 2 + 4);
        mbar_expect_tx(bar + BAR_Q, (1 + tri) * CL * D_HEAD * 4);
        mbar_expect_tx(bar + BAR_ML, n_heads * CL * 8);
#pragma unroll
        for (int i = BAR_O; i <= BAR_S; i += 8) mbar_expect_tx(bar + i, 1024);
        asm volatile("fence.mbarrier_init.release.cluster;" ::: "memory");
    }
    __syncwarp();
    cluster_arrive();
    float* sst = reinterpret_cast<float*>(sp + SM_ST);
    if (tid < 8) *reinterpret_cast<uint2*>(sp + SM_XN + D_MODEL * 2 + tid * 8) = make_uint2(0u, 0u);
    if (rank == CL - 1 && warp >= V_WARPS && warp < N_CONS_WARPS) {
        named_arrive(6, n_start);
        if (warp == V_WARPS) {
            const uint32_t ep = ll_ld(g_epoch);
            cluster_wait();
            if (lane < CL) st_async(mapa(sb + SM_EPOCH, lane), __uint_as_float(ep), mapa(bar + BAR_X, lane));
        } else {
            uint2 u[5];
#pragma unroll
            for (int i = 0; i < 5; i++) u[i] = *reinterpret_cast<const uint2*>(prm.x + i * 128 + lane * 4);
            float s = 0.f;
#pragma unroll
            for (int i = 0; i < 5; i++) s += (bf_lo(u[i].x) + bf_hi(u[i].x)) + (bf_lo(u[i].y) + bf_hi(u[i].y));
#pragma unroll
            for (int o = 16; o > 0; o >>= 1) s += __shfl_xor_sync(0xffffffffu, s, o);
            const float mean = s * (1.f / D_MODEL);
            s = 0.f;
#pragma unroll
            for (int i = 0; i < 5; i++) {
                const float a = bf_lo(u[i].x) - mean, b = bf_hi(u[i].x) - mean, c = bf_lo(u[i].y) - mean, d = bf_hi(u[i].y) - mean;
                s += fmaf(a, a, b * b) + fmaf(c, c, d * d);
            }
#pragma unroll
            for (int o = 16; o > 0; o >>= 1) s += __shfl_xor_sync(0xffffffffu, s, o);
            const float mean_b = bf16r(mean);
            float den;
            asm("sqrt.approx.f32 %0, %1;" : "=f"(den) : "f"(bf16r(bf16r(s * (1.f / D_MODEL)) + 1e-5f)));
            const float inv = rcp(bf16r(den));
#pragma unroll
            for (int i = 0; i < 5; i++) {
                const uint32_t d0 = pack_bf16(bf_lo(u[i].x) - mean_b, bf_hi(u[i].x) - mean_b);
                const uint32_t d1 = pack_bf16(bf_lo(u[i].y) - mean_b, bf_hi(u[i].y) - mean_b);
                u[i] = make_uint2(pack_bf16(bf_lo(d0) * inv, bf_hi(d0) * inv), pack_bf16(bf_lo(d1) * inv, bf_hi(d1) * inv));
            }
            cluster_wait();
#pragma unroll 1
            for (int d = 0; d < CL; d++) {
                const uint32_t dst = mapa(sb + SM_XN + lane * 8, d), mb = mapa(bar + BAR_X, d);
#pragma unroll
                for (int i = 0; i < 5; i++) st_async2(dst + i * 256, __uint_as_float(u[i].x), __uint_as_float(u[i].y), mb);
            }
        }
        __syncwarp();
    } else if (warp == N_CONS_WARPS + 1 ? rank >= V_WARPS : warp > N_CONS_WARPS && !owner) {
        named_arrive(6, n_start);
        return;
    } else {
        named_sync(6, n_start);
    }
    if (tid == 0) mbar_arrive(bar + BAR_READY);
    mbar_wait(bar + BAR_X, 0);
    const uint32_t epoch = lds32(sb + SM_EPOCH);
    const uint32_t tag = 1u + (epoch & 1u);

    if (warp == N_CONS_WARPS + 1) {
        ll_store(g_x + D_FF + pair_head(cl, 1) * D_HEAD + rank * 32 + lane, 0u);
        const bool fin = owner && rank < 4;
        const int col = oc * 64 + rank * 16 + (lane & 1) * 8 + ((lane >> 1) & 7);
        uint16_t* const out = reinterpret_cast<uint16_t*>(prm.out) + col;
        mbar_wait(bar + BAR_ML, 0);
        uint32_t xv = 0;
        if (fin) xv = reinterpret_cast<const uint16_t*>(prm.x)[col];
        float wv;
        {
            const uint32_t ma = sb + SM_ML + (lane < n_heads * CL ? lane : 0) * 8;
            const float mi = lds_f(ma);
            float m = fmaxf(mi, __shfl_xor_sync(0xffffffffu, mi, 1));
            m = fmaxf(m, __shfl_xor_sync(0xffffffffu, m, 2));
            m = fmaxf(m, __shfl_xor_sync(0xffffffffu, m, 4));
            const float ei = ex2((mi - m) * LOG2E);
            float den = ei * lds_f(ma + 4);
            den += __shfl_xor_sync(0xffffffffu, den, 1);
            den += __shfl_xor_sync(0xffffffffu, den, 2);
            den += __shfl_xor_sync(0xffffffffu, den, 4);
            wv = ei * rcp(den);
        }
#pragma unroll 1
        for (int hh = 0; hh < n_heads; hh++) {
            float w[CL];
#pragma unroll
            for (int s = 0; s < CL; s++) w[s] = __shfl_sync(0xffffffffu, wv, hh * CL + s);
            uint32_t* dst = g_x + D_FF + head_at(cl, hh, tri) * D_HEAD + rank * 32 + lane;
            const uint32_t src = sb + SM_OP + hh * 1024 + lane * 4;
            mbar_wait(bar + BAR_O + hh * 8, 0);
            float v[CL];
#pragma unroll
            for (int s = 0; s < CL; s++) v[s] = lds_f(src + s * 128);
            const float o = (fmaf(w[1], v[1], w[0] * v[0]) + fmaf(w[3], v[3], w[2] * v[2])) +
                            (fmaf(w[5], v[5], w[4] * v[4]) + fmaf(w[7], v[7], w[6] * v[6]));
            ll_store(dst, __float_as_uint(bf16r(o)) | tag);
        }
        if (fin) {
            mbar_wait(bar + BAR_G, 0);
            const uint32_t g = pack_bf16(silu_f(bf16r(lds_colsum(sb + SM_FG, lane))), 0.f);
            asm volatile("{\n.reg .pred p;\nsetp.eq.u32 p, %2, 0;\n@p st.relaxed.gpu.global.b32 [%0], %1;\n}" ::"l"(g_epoch), "r"(epoch + 1u), "r"(oc + rank + lane) : "memory");
            mbar_wait(bar + BAR_S, 0);
            uint32_t res = pack_bf16(lds_colsum(sb + SM_FS, lane), 0.f);
            asm("mul.rn.bf16x2 %0, %0, %1;" : "+r"(res) : "r"(g));
            asm("add.rn.bf16x2 %0, %0, %1;" : "+r"(res) : "r"(xv));
            if (lane < 16) *out = (uint16_t)res;
        }
        return;
    }
    if (warp >= N_CONS_WARPS + 2) {
        const int gw = warp - (N_CONS_WARPS + 2);
        mbar_wait(bar + BAR_GO, 0);
#pragma unroll 1
        for (int round = 0; round < 2; round++) {
            const int i0 = round * 4 + 2 + gw;
            const uint32_t* src0 = g_x + tail_row(rank, i0) + lane * 4;
            const uint32_t* src1 = g_x + tail_row(rank, gw) + lane * 4;
            if (round == 1) {
                named_arrive(8, N_CONS + N_GATHER);
                mbar_wait(bar + BAR_GO + 8, 0);
                mbar_wait(bar_full + (SLOT_T + 1) * 8, 0);
            }
            uint4 v0 = make_uint4(0u, 0u, 0u, 0u), v1 = v0;
            const bool second = round == 0 && gw < 2 && lane < 24;
            uint32_t miss0 = lane < 24, miss1 = second;
            unsigned n = 0;
#pragma unroll 1
            while (true) {
                ll_ld4_if(v0, src0, miss0);
                ll_ld4_if(v1, src1, miss1);
                if (ll_bad4(v0, tag) == 0) miss0 = 0;
                if (ll_bad4(v1, tag) == 0) miss1 = 0;
                if (__all_sync(0xffffffffu, (miss0 | miss1) == 0) || ++n > SPIN_LIMIT) break;
            }
            if (lane < 24)
                *reinterpret_cast<uint2*>(sp + SM_OV + i0 * 192 + lane * 8) = make_uint2(__byte_perm(v0.x, v0.y, 0x7632), __byte_perm(v0.z, v0.w, 0x7632));
            if (second)
                *reinterpret_cast<uint2*>(sp + SM_OV + gw * 192 + lane * 8) = make_uint2(__byte_perm(v1.x, v1.y, 0x7632), __byte_perm(v1.z, v1.w, 0x7632));
        }
        named_arrive(3, N_CONS + N_GATHER);
        return;
    }


    const int q4 = lane & 3, g8 = lane >> 2;
    const int rowT = (lane & 7) + ((lane >> 4) << 3), hiT = (lane >> 3) & 1;
    const uint32_t off_v = ((3 * rowT + (warp >> 1)) * 128 + ((hiT ^ ((3 * rowT + (warp >> 1)) & 7)) << 4)) ^ ((warp & 1) << 6);

    if (warp < V_WARPS) {
#pragma unroll 1
        for (int part = 0; part <= tri; part++) {
            const uint32_t xa = sb + SM_XN + ((part ? rank * 16 - 1280 : (rank & 3) * 16) + 2 * q4) * 2, xs = 128 << part;
            float acc[2][4] = {};
#pragma unroll 1
            for (int p = part * 10; p < 10 + part * 5; p++) {
                const uint32_t b0 = lds32(xa + p * xs), b1 = lds32(xa + p * xs + 16);
                mbar_wait(bar_full + (p >> 1) * 8, 0);
                uint32_t a[4];
                ldsm_x4_t(a, sb + SM_RING + p * PIECE_BYTES + off_v);
                mma_bf16(acc[0], a, b0, b1);
                ldsm_x4_t(a, sb + SM_RING + p * PIECE_BYTES + (off_v ^ 32));
                mma_bf16(acc[1], a, b0, b1);
                __syncwarp();
                if (lane == 0) mbar_arrive_n(bar_empty + (p >> 1) * 8, p == 14 ? RELEASE / V_WARPS : RELEASE / V_WARPS / 2);
            }
            const float v = pick4(acc[0][0], acc[0][2], acc[1][0], acc[1][2], q4);
            const uint32_t dst = sb + SM_QP + ((part * CL + rank) * D_HEAD + warp * 32 + q4 * 8 + g8) * 4;
#pragma unroll
            for (int d = 0; d < CL; d++) st_async(mapa(dst, d), v, mapa(bar + BAR_Q, d));
        }
        mbar_wait(bar + BAR_Q, 0);
        const float* qp = reinterpret_cast<const float*>(sp + SM_QP) + tid;
        __nv_bfloat16* qs = reinterpret_cast<__nv_bfloat16*>(sp + SM_Q) + tid;
        qs[0] = __float2bfloat16_rn((qp[0] + qp[192]) + (qp[384] + qp[576]));
        qs[(tri + 1) * D_HEAD] = __float2bfloat16_rn((qp[768] + qp[960]) + (qp[1152] + qp[1344]));
        if (tri) {
            qp += CL * D_HEAD;
            qs[D_HEAD] = __float2bfloat16_rn(((qp[0] + qp[192]) + (qp[384] + qp[576])) + ((qp[768] + qp[960]) + (qp[1152] + qp[1344])));
        }
    }
    named_sync(1, N_CONS);

    {
        const int rowN = (lane & 7) + (((lane >> 3) & 1) << 3), hiN = lane >> 4;
#pragma unroll 1
        for (int hh = 0; hh < n_heads; hh++) {
            float s0 = 0.f, s1 = 0.f;
#pragma unroll 1
            for (int i = 0; i < 2; i++) {
                const int u = hh * HEAD_TILES + i * 8 + warp, pos = pos_k + u, slot = pos & (N_SLOT - 1);
                mbar_wait(bar_full + slot * 8, (pos >> 4) & 1);
                const uint32_t tb = sb + SM_RING + slot * TILE_BYTES;
                float acc[2][2][4] = {};
#pragma unroll 1
                for (int j = 0; j < 3; j++) {
                    const int swz = u < 2 ? 0 : (3 * rowN + j) & 7;
                    const uint32_t oj = tb + (3 * rowN + j) * 128 + ((hiN ^ swz) << 4);
                    const uint32_t qa = sb + SM_Q + (hh * D_HEAD + j * 64 + 2 * q4) * 2;
#pragma unroll
                    for (int k = 0; k < 4; k++) {
                        const uint32_t b0 = lds32(qa + k * 32), b1 = lds32(qa + k * 32 + 16);
                        uint32_t a[4];
                        ldsm_x4(a, oj ^ (k << 5));
                        mma_bf16(acc[0][k & 1], a, b0, b1);
                        ldsm_x4(a, (oj + PIECE_BYTES) ^ (k << 5));
                        mma_bf16(acc[1][k & 1], a, b0, b1);
                    }
                }
                __syncwarp();
                if (lane == 0) mbar_arrive_n(bar_empty + slot * 8, RELEASE);
                const float raw = pick4(acc[0][0][0] + acc[0][1][0], acc[0][0][2] + acc[0][1][2],
                                        acc[1][0][0] + acc[1][1][0], acc[1][0][2] + acc[1][1][2], q4);
                s0 = s1;
                s1 = bf16r(bf16r(raw) * 0.07216878364870323f);
            }
            float m = fmaxf(s0, s1);
#pragma unroll
            for (int o = 16; o > 0; o >>= 1) m = fmaxf(m, __shfl_xor_sync(0xffffffffu, m, o));
            if (lane == 0) sst[hh * 8 + warp] = m;
            named_sync(1, N_CONS);
#pragma unroll
            for (int w = 0; w < 8; w++) m = fmaxf(m, sst[hh * 8 + w]);
            const float p0 = ex2((s0 - m) * LOG2E), p1 = ex2((s1 - m) * LOG2E);
            float l = p0 + p1;
#pragma unroll
            for (int o = 16; o > 0; o >>= 1) l += __shfl_xor_sync(0xffffffffu, l, o);
            if (lane == 0) sst[24 + hh * 8 + warp] = l;
            __nv_bfloat16* ps = reinterpret_cast<__nv_bfloat16*>(sp + SM_P) + hh * 512 + warp * 32 + q4 * 8 + g8;
            ps[0] = __float2bfloat16_rn(p0);
            ps[256] = __float2bfloat16_rn(p1);
        }
        named_sync(1, N_CONS);
        if (warp == 7 && lane < n_heads * CL && (lane & 7) < V_WARPS) {
            const float* st = sst + (lane & 24);
            float m = st[0], l = st[24];
#pragma unroll
            for (int w = 1; w < 8; w++) { m = fmaxf(m, st[w]); l += st[24 + w]; }
            st_async2(mapa(sb + SM_ML + ((lane & 24) + rank) * 8, lane & 7), m, l, mapa(bar + BAR_ML, lane & 7));
        }
    }

    const uint32_t off_w = (warp >> 2) * PIECE_BYTES + rowT * 128 + (((((warp & 3) << 1) | hiT) ^ (rowT & 7)) << 4);

    if (ffn) {
#pragma unroll 1
        for (int res = 0; res < 2; res++) {
            float acc[3][4] = {};
#pragma unroll 1
            for (int i = 0; i < W_TILES / 2; i++) {
                const int pos = pos_w + res * (W_TILES / 2) + i, slot = pos & (N_SLOT - 1);
                const uint32_t xa = sb + SM_XN + (i * 96 + (warp >> 2) * 48 + 2 * q4) * 2;
                mbar_wait(bar_full + slot * 8, (pos >> 4) & 1);
#pragma unroll
                for (int k = 0; k < 3; k++) {
                    uint32_t a[4];
                    ldsm_x4_t(a, sb + SM_RING + slot * TILE_BYTES + off_w + k * 2048);
                    mma_bf16(acc[k], a, lds32(xa + k * 32), lds32(xa + k * 32 + 16));
                }
                __syncwarp();
                if (lane == 0) mbar_arrive_n(bar_empty + slot * 8, RELEASE / N_CONS_WARPS);
            }
            if (q4 < 2)
                reinterpret_cast<float*>(sp + SM_FG)[res * 128 + warp * 16 + q4 * 8 + g8] =
                    q4 ? (acc[0][2] + acc[1][2]) + acc[2][2] : (acc[0][0] + acc[1][0]) + acc[2][0];
        }
        named_sync(1, N_CONS);
        if (warp >= V_WARPS) {
            const float* f = reinterpret_cast<const float*>(sp + SM_FG) + (tid & 63);
            const float h = bf16r(bf16r(silu_f(bf16r(f[0] + f[64]))) * bf16r(f[128] + f[192]));
            ll_store(g_x + (cta - CL_FFN * CL) * 64 + (tid & 63), __float_as_uint(h) | tag);
        }
    }

    if (warp < V_WARPS) {
        const uint32_t rdst = mapa(sb + SM_OP + rank * 128 + (q4 * 8 + g8) * 4, warp), rbar = mapa(bar + BAR_O, warp);
#pragma unroll 1
        for (int hh = 0; hh < n_heads; hh++) {
            float oacc[2][2][4] = {};
#pragma unroll 2
            for (int u = hh * HEAD_TILES; u < (hh + 1) * HEAD_TILES; u++) {
                const int pos = pos_v + u, slot = pos & (N_SLOT - 1);
                uint32_t ta = sb + SM_RING + slot * TILE_BYTES + off_v, tc = ta ^ 32;
                asm volatile("" : "+r"(ta), "+r"(tc));
                const uint32_t pa = sb + SM_P + (u * 32 + 2 * q4) * 2;
                const uint32_t b0 = lds32(pa), b1 = lds32(pa + 16), b2 = lds32(pa + 32), b3 = lds32(pa + 48);
                mbar_wait(bar_full + slot * 8, (pos >> 4) & 1);
                uint32_t a[4][4];
                ldsm_x4_t(a[0], ta);
                ldsm_x4_t(a[1], tc);
                ldsm_x4_t(a[2], ta + PIECE_BYTES);
                ldsm_x4_t(a[3], tc + PIECE_BYTES);
                mma_bf16(oacc[0][0], a[0], b0, b1);
                mma_bf16(oacc[1][0], a[1], b0, b1);
                mma_bf16(oacc[0][1], a[2], b2, b3);
                mma_bf16(oacc[1][1], a[3], b2, b3);
                __syncwarp();
                if (lane == 0) mbar_arrive_n(bar_empty + slot * 8, RELEASE / V_WARPS);
            }
            const float v = pick4(oacc[0][0][0] + oacc[0][1][0], oacc[0][0][2] + oacc[0][1][2],
                                  oacc[1][0][0] + oacc[1][1][0], oacc[1][0][2] + oacc[1][1][2], q4);
            st_async(rdst + hh * 1024, v, rbar + hh * 8);
        }
    }
    if (!owner) return;

    {
        const uint32_t rdst = mapa(sb + SM_FG + (rank * 2 + (warp >> 2)) * 64 + g8 * 8, warp & 3);
        const uint32_t rbar = mapa(bar + BAR_G, warp & 3);
        const uint32_t va = sb + SM_OV + ((warp >> 2) * 48 + 2 * q4) * 2, tw = sb + SM_RING + SLOT_T * TILE_BYTES + off_w;
        named_sync(8, N_CONS + N_GATHER);
        auto send = [&](const float (&acc)[3][4], uint32_t dst, uint32_t mb) {
            if (q4 == 0) st_async2(dst, (acc[0][0] + acc[1][0]) + acc[2][0], (acc[0][2] + acc[1][2]) + acc[2][2], mb);
        };
        float acc[3][4] = {};
#pragma unroll 1
        for (int i = 0; i < 6; i++) {
            uint32_t b[3][2];
#pragma unroll
            for (int k = 0; k < 3; k++) { b[k][0] = lds32(va + i * 192 + k * 32); b[k][1] = lds32(va + i * 192 + k * 32 + 16); }
            mbar_wait(bar_full + (SLOT_T + i) * 8, 0);
#pragma unroll
            for (int k = 0; k < 3; k++) {
                uint32_t a[4];
                ldsm_x4_t(a, tw + i * TILE_BYTES + k * 2048);
                mma_bf16(acc[k], a, b[k][0], b[k][1]);
            }
            if (i == 1) {
                send(acc, rdst, rbar);
#pragma unroll
                for (int k = 0; k < 3; k++) acc[k][0] = acc[k][1] = acc[k][2] = acc[k][3] = 0.f;
            }
        }
        const uint32_t hb = warp < 4 ? bar_full + (SLOT_T + 6) * 8 : bar + BAR_HALF;
        uint32_t a[4][3][4], b[4][3][2];
        named_sync(3, N_CONS + N_GATHER);
#pragma unroll
        for (int i = 0; i < 4; i++)
#pragma unroll
            for (int k = 0; k < 3; k++) { b[i][k][0] = lds32(va + (6 + i) * 192 + k * 32); b[i][k][1] = lds32(va + (6 + i) * 192 + k * 32 + 16); }
#pragma unroll
        for (int i = 0; i <= 4; i++) {
            if (i < 4) {
                mbar_wait(hb + i * 8, 0);
#pragma unroll
                for (int k = 0; k < 3; k++) ldsm_x4_t(a[i][k], tw + (6 + i) * TILE_BYTES + k * 2048);
            }
            if (i >= 1) {
#pragma unroll
                for (int k = 0; k < 3; k++) mma_bf16(acc[k], a[i - 1][k], b[i - 1][k][0], b[i - 1][k][1]);
            }
        }
        send(acc, rdst + (SM_FS - SM_FG), rbar + (BAR_S - BAR_G));
    }
}

typedef CUresult (*EncodeTiledFn)(CUtensorMap*, CUtensorMapDataType, cuuint32_t, void*, const cuuint64_t*,
                                  const cuuint64_t*, const cuuint32_t*, const cuuint32_t*, CUtensorMapInterleave,
                                  CUtensorMapSwizzle, CUtensorMapL2promotion, CUtensorMapFloatOOBfill);

void encode_map(EncodeTiledFn fn, CUtensorMap* m, const void* base, cuuint64_t rows, cuuint64_t cols, cuuint32_t b1, cuuint32_t b2) {
    const cuuint64_t dims[3] = {64, cols / 64, rows};
    const cuuint64_t strides[2] = {128, cols * 2};
    const cuuint32_t box[3] = {64, b1, b2};
    const cuuint32_t estr[3] = {1, 1, 1};
    fn(m, CU_TENSOR_MAP_DATA_TYPE_BFLOAT16, 3, const_cast<void*>(base), dims, strides, box, estr,
       CU_TENSOR_MAP_INTERLEAVE_NONE, CU_TENSOR_MAP_SWIZZLE_128B, CU_TENSOR_MAP_L2_PROMOTION_NONE,
       CU_TENSOR_MAP_FLOAT_OOB_FILL_NONE);
}

}

extern "C" void kernel_launch(void* const* d_in, const int* in_sizes, int n_in, void* d_out, int out_size) {
    (void)in_sizes; (void)n_in; (void)out_size;
    static EncodeTiledFn encode = nullptr;
    static double pace_scale = 1.0;
    static void* scratch = nullptr;
    if (!encode) {
        int dev = 0, mem_khz = 0, bus_bits = 0;
        cudaGetDevice(&dev);
        cudaDeviceGetAttribute(&mem_khz, cudaDevAttrMemoryClockRate, dev);
        cudaDeviceGetAttribute(&bus_bits, cudaDevAttrGlobalMemoryBusWidth, dev);
        const double peak_gbs = 2.0 * mem_khz * 1e-6 * bus_bits / 8.0;
        if (peak_gbs > 0.0) pace_scale = PACE_REF_GBS / peak_gbs;
        void* fn = nullptr;
        cudaDriverEntryPointQueryResult qr;
        cudaGetDriverEntryPoint("cuTensorMapEncodeTiled", &fn, cudaEnableDefault, &qr);
        encode = reinterpret_cast<EncodeTiledFn>(fn);
        cudaFuncSetAttribute(fused_decode_kernel, cudaFuncAttributeMaxDynamicSharedMemorySize, SM_ALLOC);
        cudaGetSymbolAddress(&scratch, g_scratch);
    }
    CUtensorMap tm_k, tm_v, tm_wq, tm_w1, tm_w3, tm_wo, tm_w2;
    encode_map(encode, &tm_k, d_in[1], (cuuint64_t)N_HEAD * SEQ, D_HEAD, 3, 32);
    encode_map(encode, &tm_v, d_in[2], (cuuint64_t)N_HEAD * SEQ, D_HEAD, 3, 32);
    encode_map(encode, &tm_wq, d_in[3], D_MODEL, N_HEAD * D_HEAD, 3, 16);
    encode_map(encode, &tm_w1, d_in[6], D_MODEL, D_FF, 1, 96);
    encode_map(encode, &tm_w3, d_in[7], D_MODEL, D_FF, 1, 96);
    encode_map(encode, &tm_wo, d_in[4], N_HEAD * D_HEAD, D_MODEL, 1, 48);
    encode_map(encode, &tm_w2, d_in[8], D_FF, D_MODEL, 1, 48);
    Params prm;
    prm.x = static_cast<const __nv_bfloat16*>(d_in[0]);
    prm.out = static_cast<__nv_bfloat16*>(d_out);
    prm.k = static_cast<const __nv_bfloat16*>(d_in[1]) + (size_t)(SEQ - WIN) * D_HEAD;
    prm.scratch = static_cast<uint32_t*>(scratch);
    auto step = [&](double pace, double bytes, int pieces) { return (uint16_t)(8.0 * pace * pace_scale * bytes / (128.0 * TILE_BYTES) / pieces); };
    const double b_wq = 2.0 * D_MODEL * N_HEAD * D_HEAD;
    const double b_mid = 4.0 * N_HEAD * WIN * D_HEAD - 2.0 * N_CTA * TILE_BYTES + 4.0 * D_MODEL * D_FF;
    const double b_tail = 2.0 * D_MODEL * (D_FF + N_HEAD * D_HEAD);
    prm.step_wq2 = step(PACE_HEAD, b_wq, 10);
    prm.step_wq3 = step(PACE_HEAD, b_wq, 15);
    prm.step_own = step(PACE_MID, b_mid, 4 * HEAD_TILES - 2);
    prm.step_ffn = step(PACE_MID, b_mid, 4 * HEAD_TILES - 2 + W_TILES);
    prm.step_tri = step(PACE_MID, b_mid, 6 * HEAD_TILES - 2);
    prm.step_tail = step(PACE_TAIL, b_tail, TAIL_TILES);
    prm.late = (uint16_t)(4096.0 * PACE_LATE / PACE_MID + 0.5);
    prm.pad = 0;
    fused_decode_kernel<<<N_CTA, N_THREADS, SM_ALLOC, cudaStreamPerThread>>>(prm, tm_wq, tm_w1, tm_w3, tm_k, tm_v, tm_wo, tm_w2);
}
```
